```python
import torch

def _softmax(x, axis=-1):
    return torch.softmax(x, dim=axis)
def _gelu(x):
    return torch.nn.functional.gelu(x, approximate="tanh")
def _silu(x):
    return torch.nn.functional.silu(x)
def _sigmoid(x):
    return torch.sigmoid(x)
def _layernorm(x, axis=-1, eps=1e-5):
    m = x.mean(dim=axis, keepdim=True)
    v = x.var(dim=axis, keepdim=True, unbiased=False)
    return (x - m) / torch.sqrt(v + eps)
def _scatter_add(tgt, idx, src, axis=0):
    return tgt.clone().index_add_(axis, idx, src)
def _segment_sum(src, seg, n):
    out = torch.zeros((n,) + src.shape[1:], dtype=src.dtype)
    return out.index_add_(0, seg, src)
def _pad(x, pw):
    flat = tuple(v for pair in reversed(pw) for v in pair)
    return torch.nn.functional.pad(x, flat)

kernel_name = 'gather_scatter__edge_featured_mpnn_mpnn__graph'

def setup_inputs():

    _w = (lambda a: (lambda t: t.to(torch.bfloat16) if t.is_floating_point() else t)(torch.as_tensor(a)))
    N, deg, D, De = 12500, 64, 64, max(0, 1)
    E = N * deg
    H = 2 * D
    return {
        "x": _w((lambda *s: torch.randn(*s, dtype=torch.bfloat16) * 0.05)(N, D)),
        "e_attr": _w((lambda *s: torch.randn(*s, dtype=torch.bfloat16) * 1.6)(E, De)),
        "src": _w((lambda lo, hi, *s: torch.randint(lo, hi, s))(0, N, E).to(torch.int64)),
        "dst": _w((lambda lo, hi, *s: torch.randint(lo, hi, s))(0, N, E).to(torch.int64)),
        "w1": _w((lambda *s: torch.randn(*s, dtype=torch.bfloat16) * 1.6)(2 * D + De, H) * (1.0 / (2 * D + De) ** 0.5)),
        "b1": _w((lambda *s: torch.randn(*s, dtype=torch.bfloat16) * 1.6)(H) * 0.01),
        "w2": _w((lambda *s: torch.randn(*s, dtype=torch.bfloat16) * 0.05)(H, D) * (1.0 / H ** 0.5)),
        "b2": _w((lambda *s: torch.randn(*s, dtype=torch.bfloat16) * 0.05)(D) * 0.01),
    }

def reference(x, e_attr, src, dst, w1, b1, w2, b2):
    N, D = x.shape
    h_src = x[src]
    h_dst = x[dst]
    m_in = torch.concatenate([h_src, h_dst, e_attr], axis=-1)
    h = _silu(m_in @ w1 + b1)
    msg = h @ w2 + b2
    return _segment_sum(msg, dst, N)
```

```cpp
#include <cuda_runtime.h>
#include <cuda_bf16.h>
#include <stdint.h>

#define DEVI __device__ __forceinline__

namespace {

constexpr int N_NODES = 12500;
constexpr int N_EDGES = 800000;
constexpr int NB = 132;
constexpr int NT = 768;
constexpr int NW = NT / 32;
constexpr int QUADS = N_EDGES / 4;
constexpr int CHUNK = 6064;
constexpr uint32_t OWN_M = 177168;
constexpr int MAXN = 96;
constexpr int RUNS_PER_WARP = 6;
constexpr int LPR = 3;
constexpr int LIST_CAP = NB * 32 * LPR + MAXN * 4 + 32;
constexpr int FLAG_STRIDE = 136;
constexpr uint32_t DUMMY_REC = N_NODES;
constexpr uint32_t END_FLAG = 0x8000u;
constexpr int S_STRIDE = 144;

constexpr int SM_STAGE = 0;
constexpr int SM_S = 0;
constexpr int SM_W1 = 55296;
constexpr int SM_LIST = 55296;
constexpr int SM_Q = SM_LIST + LIST_CAP * 4;
constexpr int SM_W2 = SM_Q + (MAXN + 1) * 256;
constexpr int SM_HIST = SM_W2 + 16384;
constexpr int SM_BASE = SM_HIST + 640;
constexpr int SM_HIST2 = SM_BASE + 640;
constexpr int SM_BASE2 = SM_HIST2 + 384;
constexpr int SM_DEG = SM_BASE2 + 400;
constexpr int SM_MISC = SM_DEG + 384;
constexpr int SM_TOTAL = SM_MISC + 16;

__device__ uint4 g_P[(N_NODES + 1) * 16];
__device__ uint4 g_rec[NB * CHUNK / 2];
__device__ uint2 g_flag[NB * FLAG_STRIDE];
__device__ float g_part[NB * NT * 8];
__device__ uint32_t g_epoch;
DEVI void stamp(int) {}

DEVI uint32_t smem_u32(const void* p) { return (uint32_t)__cvta_generic_to_shared(p); }
DEVI void cp_async16(uint32_t dst, const void* src) {
    asm volatile("cp.async.cg.shared.global [%0],[%1],16;" ::"r"(dst), "l"(src) : "memory");
}
DEVI uint4 ldg_nc128(const void* p) {
    uint4 v;
    asm volatile("ld.global.nc.L1::no_allocate.v4.u32 {%0,%1,%2,%3},[%4];" : "=r"(v.x), "=r"(v.y), "=r"(v.z), "=r"(v.w) : "l"(p));
    return v;
}
DEVI uint2 ldg_nc64(const void* p) {
    uint2 v;
    asm volatile("ld.global.nc.L1::no_allocate.v2.u32 {%0,%1},[%2];" : "=r"(v.x), "=r"(v.y) : "l"(p));
    return v;
}
DEVI uint4 ldg128(const void* p) {
    uint4 v;
    asm volatile("ld.global.v4.u32 {%0,%1,%2,%3},[%4];" : "=r"(v.x), "=r"(v.y), "=r"(v.z), "=r"(v.w) : "l"(p));
    return v;
}
DEVI void ldsm4t(uint32_t& r0, uint32_t& r1, uint32_t& r2, uint32_t& r3, uint32_t a) {
    asm volatile("ldmatrix.sync.aligned.m8n8.x4.trans.shared.b16 {%0,%1,%2,%3},[%4];"
                 : "=r"(r0), "=r"(r1), "=r"(r2), "=r"(r3) : "r"(a) : "memory");
}
DEVI void mma_bf16(float (&c)[4], uint32_t a0, uint32_t a1, uint32_t a2, uint32_t a3, uint32_t b0, uint32_t b1) {
    asm volatile("mma.sync.aligned.m16n8k16.row.col.f32.bf16.bf16.f32 {%0,%1,%2,%3},{%4,%5,%6,%7},{%8,%9},{%0,%1,%2,%3};"
                 : "+f"(c[0]), "+f"(c[1]), "+f"(c[2]), "+f"(c[3])
                 : "r"(a0), "r"(a1), "r"(a2), "r"(a3), "r"(b0), "r"(b1));
}
DEVI uint32_t pack_bf16(float lo, float hi) {
    uint32_t r;
    asm("cvt.rn.bf16x2.f32 %0,%1,%2;" : "=r"(r) : "f"(hi), "f"(lo));
    return r;
}
DEVI float bf_lo(uint32_t v) { return __uint_as_float(v << 16); }
DEVI float bf_hi(uint32_t v) { return __uint_as_float(v & 0xffff0000u); }
DEVI __nv_bfloat162 as_bf2(uint32_t v) { return *reinterpret_cast<__nv_bfloat162*>(&v); }
DEVI uint32_t as_u32(__nv_bfloat162 v) { return *reinterpret_cast<uint32_t*>(&v); }
DEVI uint32_t tanh_bf2(uint32_t a) {
    uint32_t d;
    asm("tanh.approx.bf16x2 %0,%1;" : "=r"(d) : "r"(a));
    return d;
}
DEVI int node_begin(int b) { return (int)((((uint32_t)b << 24) + OWN_M - 1) / OWN_M); }

DEVI void edge_act(uint32_t rec, const uint4& p, const uint32_t (&w)[4], const uint32_t (&q)[4], __nv_bfloat162 (&s)[4]) {
    const __nv_bfloat162 e2 = __high2bfloat162(as_bf2(rec));
    const uint32_t pw[4] = {p.x, p.y, p.z, p.w};
#pragma unroll
    for (int i = 0; i < 4; i++) {
        __nv_bfloat162 u = __hadd2(__hfma2(e2, as_bf2(w[i]), as_bf2(q[i])), as_bf2(pw[i]));
        __nv_bfloat162 t = as_bf2(tanh_bf2(as_u32(u)));
        s[i] = __hfma2(u, t, u);
    }
}

__global__ void __launch_bounds__(NT, 1)
mpnn_kernel(const __nv_bfloat16* __restrict__ x, const __nv_bfloat16* __restrict__ ea,
            const int* __restrict__ src, const int* __restrict__ dst,
            const __nv_bfloat16* __restrict__ w1, const __nv_bfloat16* __restrict__ b1,
            const __nv_bfloat16* __restrict__ w2, const __nv_bfloat16* __restrict__ b2,
            __nv_bfloat16* __restrict__ out) {
    extern __shared__ __align__(128) uint8_t smem[];
    const uint32_t sb = smem_u32(smem);
    const int tid = threadIdx.x, lane = tid & 31, warp = tid >> 5;
    const int b = blockIdx.x;
    const int g = lane >> 2, t = lane & 3;
    const int n0 = node_begin(b);
    const int nn = min(node_begin(b + 1), N_NODES) - n0;
    uint32_t* hist = reinterpret_cast<uint32_t*>(smem + SM_HIST);
    uint32_t* base = reinterpret_cast<uint32_t*>(smem + SM_BASE);
    uint32_t* hist2 = reinterpret_cast<uint32_t*>(smem + SM_HIST2);
    uint32_t* base2 = reinterpret_cast<uint32_t*>(smem + SM_BASE2);
    uint32_t* sdeg = reinterpret_cast<uint32_t*>(smem + SM_DEG);
    uint32_t* misc = reinterpret_cast<uint32_t*>(smem + SM_MISC);
    uint32_t* list = reinterpret_cast<uint32_t*>(smem + SM_LIST);
    stamp(0);

    uint32_t epoch;
    asm volatile("ld.relaxed.gpu.global.u32 %0,[%1];" : "=r"(epoch) : "l"(&g_epoch) : "memory");
    const int mt = warp >> 2, nq = warp & 3;
    uint4 xa[2][2];
#pragma unroll
    for (int h = 0; h < 2; h++) {
        const int row = min(n0 + mt * 16 + g + 8 * h, N_NODES - 1);
        const uint8_t* xp = reinterpret_cast<const uint8_t*>(x) + row * 128 + t * 32;
        xa[h][0] = __ldg(reinterpret_cast<const uint4*>(xp));
        xa[h][1] = __ldg(reinterpret_cast<const uint4*>(xp + 16));
    }
    for (int i = tid; i < 128 * 16; i += NT) {
        const int r = i >> 4, c = i & 15;
        cp_async16(sb + SM_W1 + r * 256 + ((c ^ (((r >> 4) & 3) * 2 + (r & 1))) << 4),
                   reinterpret_cast<const uint8_t*>(w1) + i * 16);
    }
    asm volatile("cp.async.commit_group;" ::: "memory");
    const int q0 = (int)((long long)b * QUADS / NB), q1 = (int)((long long)(b + 1) * QUADS / NB);
    const bool has2 = q0 + NT + tid < q1;
    uint4 vd[2], vs[2];
    uint2 ve[2];
    vd[0] = ldg_nc128(reinterpret_cast<const uint4*>(dst) + q0 + tid);
    if (has2) vd[1] = ldg_nc128(reinterpret_cast<const uint4*>(dst) + q0 + NT + tid);
    vs[0] = ldg_nc128(reinterpret_cast<const uint4*>(src) + q0 + tid);
    if (has2) vs[1] = ldg_nc128(reinterpret_cast<const uint4*>(src) + q0 + NT + tid);
    ve[0] = ldg_nc64(reinterpret_cast<const uint2*>(ea) + q0 + tid);
    if (has2) ve[1] = ldg_nc64(reinterpret_cast<const uint2*>(ea) + q0 + NT + tid);
    for (int i = tid; i < 128 * 8; i += NT) {
        const int rho = i >> 3, c = i & 7;
        const int s = rho >> 4, hi = (rho >> 3) & 1, r = rho & 7;
        const int pos = 16 * s + 4 * (r >> 1) + 2 * hi + (r & 1);
        const int ch = (pos & 64) + 8 * ((pos & 15) >> 1) + 2 * ((pos & 63) >> 4) + (pos & 1);
        cp_async16(sb + SM_W2 + rho * 128 + ((c ^ r) << 4), reinterpret_cast<const uint8_t*>(w2) + ch * 128 + c * 16);
    }
    asm volatile("cp.async.commit_group;" ::: "memory");
    if (tid < 160) hist[tid] = 0;
    if (tid < MAXN) { hist2[tid] = 0; sdeg[tid] = 0; }
    if (tid == 0) misc[0] = 0;
    if (b == 0 && tid < 16) g_P[N_NODES * 16 + tid] = make_uint4(0xff00ff00u, 0xff00ff00u, 0xff00ff00u, 0xff00ff00u);
    asm volatile("cp.async.wait_group 1;" ::: "memory");
    __syncthreads();
    stamp(1);

    {
        const int r = lane & 7, hi = (lane >> 3) & 1, half = nq & 1;
        const uint32_t* xw0 = reinterpret_cast<const uint32_t*>(&xa[0][0]);
        const uint32_t* xw1 = reinterpret_cast<const uint32_t*>(&xa[1][0]);
        const int row0 = mt * 16 + g;
#pragma unroll
        for (int jh = 0; jh < 2; jh++) {
            float c[4][4];
#pragma unroll
            for (int j = 0; j < 4; j++) c[j][0] = c[j][1] = c[j][2] = c[j][3] = 0.f;
#pragma unroll
            for (int s = 0; s < 4; s++) {
                const int k = (nq >> 1) * 64 + 16 * (r >> 1) + 4 * s + 2 * hi + (r & 1);
#pragma unroll
                for (int jp = 0; jp < 2; jp++) {
                    const int chunk = half * 8 + jh * 4 + jp * 2 + (lane >> 4);
                    uint32_t b0, b1r, b2r, b3;
                    ldsm4t(b0, b1r, b2r, b3, sb + SM_W1 + k * 256 + ((chunk ^ r) << 4));
                    mma_bf16(c[jp * 2], xw0[2 * s], xw1[2 * s], xw0[2 * s + 1], xw1[2 * s + 1], b0, b1r);
                    mma_bf16(c[jp * 2 + 1], xw0[2 * s], xw1[2 * s], xw0[2 * s + 1], xw1[2 * s + 1], b2r, b3);
                }
            }
            uint32_t o0[4], o1[4];
#pragma unroll
            for (int j = 0; j < 4; j++) {
                float a0 = 0.f, a1 = 0.f;
                if (nq >= 2) {
                    const uint32_t bb = __ldg(reinterpret_cast<const uint32_t*>(b1) + half * 32 + (jh * 4 + j) * 4 + t);
                    a0 = bf_lo(bb); a1 = bf_hi(bb);
                }
                o0[j] = pack_bf16(0.5f * (c[j][0] + a0), 0.5f * (c[j][1] + a1));
                o1[j] = pack_bf16(0.5f * (c[j][2] + a0), 0.5f * (c[j][3] + a1));
            }
            const int chunk = half * 8 + t * 2 + jh;
            if (nq < 2) {
                if (row0 < nn) g_P[(n0 + row0) * 16 + chunk] = make_uint4(o0[0], o0[1], o0[2], o0[3]);
                if (row0 + 8 < nn) g_P[(n0 + row0 + 8) * 16 + chunk] = make_uint4(o1[0], o1[1], o1[2], o1[3]);
            } else {
                *reinterpret_cast<uint4*>(smem + SM_Q + row0 * 256 + chunk * 16) = make_uint4(o0[0], o0[1], o0[2], o0[3]);
                *reinterpret_cast<uint4*>(smem + SM_Q + (row0 + 8) * 256 + chunk * 16) = make_uint4(o1[0], o1[1], o1[2], o1[3]);
            }
        }
    }
    stamp(2);

    {
        uint32_t key[8];
        const uint32_t* dd = reinterpret_cast<const uint32_t*>(vd);
        const uint32_t* ss = reinterpret_cast<const uint32_t*>(vs);
        const uint32_t* ee = reinterpret_cast<const uint32_t*>(ve);
#pragma unroll
        for (int i = 0; i < 8; i++) {
            if (i < 4 || has2) {
                const uint32_t own = (dd[i] * OWN_M) >> 24;
                key[i] = (own << 16) | atomicAdd(&hist[own], 1u);
            }
        }
        __syncthreads();
        stamp(3);
        {
            uint32_t c[5], sum = 0;
#pragma unroll
            for (int i = 0; i < 5; i++) { c[i] = hist[lane * 5 + i]; sum += c[i]; }
            uint32_t inc = sum;
#pragma unroll
            for (int o = 1; o < 32; o <<= 1) {
                const uint32_t v = __shfl_up_sync(0xffffffffu, inc, o);
                if (lane >= o) inc += v;
            }
            uint32_t run = inc - sum;
#pragma unroll
            for (int i = 0; i < 5; i++) { base[lane * 5 + i] = run; run += c[i]; }
            __syncwarp();
        }
        uint2* stage = reinterpret_cast<uint2*>(smem + SM_STAGE);
#pragma unroll
        for (int i = 0; i < 8; i++) {
            if (i < 4 || has2) {
                const uint32_t pos = base[key[i] >> 16] + (key[i] & 0xffffu);
                const uint32_t ew = ee[i >> 1];
                const uint32_t rec = __byte_perm(ss[i], ew, (i & 1) ? 0x7610 : 0x5410);
                stage[pos] = make_uint2(rec, dd[i]);
            }
        }
        __syncthreads();
        stamp(4);
        const int nv = (q1 - q0) * 2;
        for (int i = tid; i < nv; i += NT)
            g_rec[b * (CHUNK / 2) + i] = *reinterpret_cast<const uint4*>(smem + SM_STAGE + i * 16);
        __syncthreads();
        epoch += 1;
        if (tid < NB) {
            const uint32_t v = base[tid] | (hist[tid] << 16);
            asm volatile("fence.acq_rel.gpu;" ::: "memory");
            asm volatile("st.relaxed.gpu.global.v2.u32 [%0],{%1,%2};" ::"l"(&g_flag[tid * FLAG_STRIDE + b]), "r"(v), "r"(epoch) : "memory");
        }
    }
    stamp(5);

    uint32_t runinfo = 0;
    {
        const int p = warp + NW * lane;
        if (lane < RUNS_PER_WARP && p < NB) {
            uint32_t tag;
            int spins = 0;
            do {
                asm volatile("ld.relaxed.gpu.global.v2.u32 {%0,%1},[%2];" : "=r"(runinfo), "=r"(tag) : "l"(&g_flag[b * FLAG_STRIDE + p]) : "memory");
                if (++spins > (1 << 22)) __trap();
            } while (tag != epoch);
            atomicMax(&misc[0], runinfo >> 16);
        }
        asm volatile("fence.acq_rel.gpu;" ::: "memory");
        __syncwarp();
    }
    stamp(6);

    const int l16 = lane & 15;
    uint32_t wv[4];
#pragma unroll
    for (int i = 0; i < 4; i++) {
        const uint32_t v = __ldg(reinterpret_cast<const uint32_t*>(w1 + 128 * 128) + (l16 >> 3) * 32 + ((l16 & 1) * 4 + i) * 4 + ((l16 & 7) >> 1));
        wv[i] = pack_bf16(0.5f * bf_lo(v), 0.5f * bf_hi(v));
    }
    const uint8_t* Pl = reinterpret_cast<const uint8_t*>(g_P) + l16 * 16;

    for (int round = 0;; round++) {
        uint32_t rw[RUNS_PER_WARP][LPR], rk[RUNS_PER_WARP][LPR];
#pragma unroll
        for (int i = 0; i < RUNS_PER_WARP; i++) {
            const uint32_t ri = __shfl_sync(0xffffffffu, runinfo, i);
            const int cnt = (int)(ri >> 16) - round * (32 * LPR);
            const uint2* rp = reinterpret_cast<const uint2*>(g_rec) + (warp + NW * i) * CHUNK + (ri & 0xffffu) + round * (32 * LPR) + lane;
#pragma unroll
            for (int j = 0; j < LPR; j++) {
                rk[i][j] = 0xffffffffu;
                if (lane + 32 * j < cnt) {
                    asm volatile("ld.global.L1::no_allocate.v2.u32 {%0,%1},[%2];" : "=r"(rw[i][j]), "=r"(rk[i][j]) : "l"(rp + 32 * j) : "memory");
                }
            }
        }
#pragma unroll
        for (int i = 0; i < RUNS_PER_WARP; i++) {
#pragma unroll
            for (int j = 0; j < LPR; j++) {
                if (rk[i][j] != 0xffffffffu) {
                    const uint32_t nl = rk[i][j] - n0;
                    rk[i][j] = (nl << 16) | atomicAdd(&hist2[nl], 1u);
                }
            }
        }
        __syncthreads();
        stamp(7);
        const bool more = misc[0] > (uint32_t)((round + 1) * (32 * LPR));
        uint32_t TG;
        uint32_t gb[3];
        {
            uint32_t c[3], pg[3], sum = 0;
#pragma unroll
            for (int i = 0; i < 3; i++) {
                c[i] = hist2[lane * 3 + i];
                pg[i] = (lane * 3 + i < nn) ? max((c[i] + 3) >> 2, 1u) : 0u;
                sum += pg[i];
            }
            uint32_t inc = sum;
#pragma unroll
            for (int o = 1; o < 32; o <<= 1) {
                const uint32_t v = __shfl_up_sync(0xffffffffu, inc, o);
                if (lane >= o) inc += v;
            }
            TG = __shfl_sync(0xffffffffu, inc, 31);
            uint32_t run = inc - sum;
#pragma unroll
            for (int i = 0; i < 3; i++) {
                gb[i] = run;
                base2[lane * 3 + i] = (run * 4) | ((pg[i] * 4 - 1) << 16);
                if (warp == i && pg[i]) {
                    for (uint32_t k = c[i]; k < pg[i] * 4; k++)
                        list[run * 4 + k] = DUMMY_REC | ((k == pg[i] * 4 - 1) ? END_FLAG : 0u);
                    sdeg[lane * 3 + i] += c[i];
                }
                run += pg[i];
            }
            if (warp == 3 && lane < 16) list[TG * 4 + lane] = DUMMY_REC;
            __syncwarp();
        }
#pragma unroll
        for (int i = 0; i < RUNS_PER_WARP; i++) {
#pragma unroll
            for (int j = 0; j < LPR; j++) {
                if (rk[i][j] != 0xffffffffu) {
                    const uint32_t bb = base2[rk[i][j] >> 16];
                    const uint32_t rank = rk[i][j] & 0xffffu;
                    list[(bb & 0xffffu) + rank] = rw[i][j] | ((rank == (bb >> 16)) ? END_FLAG : 0u);
                }
            }
        }
        const uint32_t T2 = (TG + 1) >> 1;
        const uint32_t per = T2 / NW, rem = T2 - per * NW;
        const int cnt = per + ((uint32_t)warp < rem);
        const uint32_t gs0 = 2 * (warp * per + min((uint32_t)warp, rem));
        int node;
        {
            const uint32_t gs1 = gs0 + cnt;
            int c0 = 0, c1 = 0;
#pragma unroll
            for (int i = 0; i < 3; i++) {
                const bool valid = lane * 3 + i < nn;
                c0 += __popc(__ballot_sync(0xffffffffu, valid && gb[i] <= gs0));
                c1 += __popc(__ballot_sync(0xffffffffu, valid && gb[i] <= gs1));
            }
            node = (lane < 16 ? c0 : c1) - 1;
        }
        __syncthreads();
        stamp(8);
        if (tid < MAXN) hist2[tid] = 0;

        float acc[8];
#pragma unroll
        for (int i = 0; i < 8; i++) acc[i] = 0.f;
        {
            const uint4* rp = reinterpret_cast<const uint4*>(list) + gs0 + (lane >> 4) * cnt;
            const uint8_t* qp = smem + SM_Q + node * 256 + l16 * 16;
            float* sp = reinterpret_cast<float*>(smem + SM_S) + node * S_STRIDE + l16 * 8;
            uint32_t qv[4];
            {
                const uint4 v = *reinterpret_cast<const uint4*>(qp);
                qv[0] = v.x; qv[1] = v.y; qv[2] = v.z; qv[3] = v.w;
            }
            uint4 rA = rp[0], rB = rp[1], A[4], B[4];
#define LOAD_GROUP(buf, r)                                   \
    {                                                        \
        buf[0] = ldg128(Pl + (r.x & 0x3fffu) * 256u);        \
        buf[1] = ldg128(Pl + (r.y & 0x3fffu) * 256u);        \
        buf[2] = ldg128(Pl + (r.z & 0x3fffu) * 256u);        \
        buf[3] = ldg128(Pl + (r.w & 0x3fffu) * 256u);        \
    }
#define COMPUTE_GROUP(buf, r)                                                              \
    {                                                                                      \
        __nv_bfloat162 s0[4], s1[4], s2[4], s3[4];                                         \
        edge_act(r.x, buf[0], wv, qv, s0);                                                 \
        edge_act(r.y, buf[1], wv, qv, s1);                                                 \
        edge_act(r.z, buf[2], wv, qv, s2);                                                 \
        edge_act(r.w, buf[3], wv, qv, s3);                                                 \
        _Pragma("unroll") for (int i = 0; i < 4; i++) {                                    \
            const uint32_t v = as_u32(__hadd2(__hadd2(s0[i], s1[i]), __hadd2(s2[i], s3[i]))); \
            acc[2 * i] += bf_lo(v);                                                        \
            acc[2 * i + 1] += bf_hi(v);                                                    \
        }                                                                                  \
        if (r.w & END_FLAG) {                                                              \
            *reinterpret_cast<float4*>(sp) = make_float4(acc[0], acc[1], acc[2], acc[3]);  \
            *reinterpret_cast<float4*>(sp + 4) = make_float4(acc[4], acc[5], acc[6], acc[7]); \
            sp += S_STRIDE;                                                                \
            qp += 256;                                                                     \
            const uint4 v = *reinterpret_cast<const uint4*>(qp);                           \
            qv[0] = v.x; qv[1] = v.y; qv[2] = v.z; qv[3] = v.w;                            \
            _Pragma("unroll") for (int i = 0; i < 8; i++) acc[i] = 0.f;                    \
        }                                                                                  \
    }
            LOAD_GROUP(A, rA);
            int left = cnt;
#pragma unroll 1
            while (left >= 2) {
                LOAD_GROUP(B, rB);
                const uint4 rC = rp[2];
                COMPUTE_GROUP(A, rA);
                rA = rC;
                LOAD_GROUP(A, rA);
                const uint4 rD = rp[3];
                COMPUTE_GROUP(B, rB);
                rB = rD;
                rp += 2;
                left -= 2;
            }
            if (left) COMPUTE_GROUP(A, rA);
            stamp(9);
            __syncthreads();
            stamp(10);
            if (sp < reinterpret_cast<float*>(smem + SM_S) + nn * S_STRIDE) {
#pragma unroll
                for (int i = 0; i < 8; i++) atomicAdd(sp + i, acc[i]);
            }
        }
        asm volatile("cp.async.wait_group 0;" ::: "memory");
        __syncthreads();
        stamp(11);

        {
            float c[2][4];
#pragma unroll
            for (int j = 0; j < 2; j++) c[j][0] = c[j][1] = c[j][2] = c[j][3] = 0.f;
            const int row0 = mt * 16 + g;
            const float* s0 = reinterpret_cast<const float*>(smem + SM_S) + row0 * S_STRIDE + 4 * t;
            const int r = lane & 7;
            const uint32_t wa = sb + SM_W2 + (lane & 15) * 128 + (((nq * 2 + (lane >> 4)) ^ r) << 4);
#pragma unroll
            for (int s = 0; s < 8; s++) {
                const float4 u = *reinterpret_cast<const float4*>(s0 + 16 * s);
                const float4 v = *reinterpret_cast<const float4*>(s0 + 8 * S_STRIDE + 16 * s);
                uint32_t b0, b1r, b2r, b3;
                ldsm4t(b0, b1r, b2r, b3, wa + s * 2048);
                const uint32_t a0 = pack_bf16(u.x, u.y), a2 = pack_bf16(u.z, u.w);
                const uint32_t a1 = pack_bf16(v.x, v.y), a3 = pack_bf16(v.z, v.w);
                const uint32_t l0 = pack_bf16(u.x - bf_lo(a0), u.y - bf_hi(a0)), l2 = pack_bf16(u.z - bf_lo(a2), u.w - bf_hi(a2));
                const uint32_t l1 = pack_bf16(v.x - bf_lo(a1), v.y - bf_hi(a1)), l3 = pack_bf16(v.z - bf_lo(a3), v.w - bf_hi(a3));
                mma_bf16(c[0], a0, a1, a2, a3, b0, b1r);
                mma_bf16(c[1], a0, a1, a2, a3, b2r, b3);
                mma_bf16(c[0], l0, l1, l2, l3, b0, b1r);
                mma_bf16(c[1], l0, l1, l2, l3, b2r, b3);
            }
            float* part = g_part + (b * NT + tid) * 8;
            if (round > 0) {
#pragma unroll
                for (int i = 0; i < 8; i++) c[i >> 2][i & 3] += part[i];
            }
            if (more) {
#pragma unroll
                for (int i = 0; i < 8; i++) part[i] = c[i >> 2][i & 3];
            } else {
                const float d0 = (float)sdeg[row0], d1 = (float)sdeg[row0 + 8];
#pragma unroll
                for (int j = 0; j < 2; j++) {
                    const int colw = nq * 8 + j * 4 + t;
                    const uint32_t bb = __ldg(reinterpret_cast<const uint32_t*>(b2) + colw);
                    uint32_t* o = reinterpret_cast<uint32_t*>(out) + (n0 + row0) * 32 + colw;
                    if (row0 < nn) o[0] = pack_bf16(fmaf(d0, bf_lo(bb), c[j][0]), fmaf(d0, bf_hi(bb), c[j][1]));
                    if (row0 + 8 < nn) o[8 * 32] = pack_bf16(fmaf(d1, bf_lo(bb), c[j][2]), fmaf(d1, bf_hi(bb), c[j][3]));
                }
            }
        }
        if (!more) break;
        __syncthreads();
    }
    if (b == 0 && tid == 0) g_epoch = epoch;
    stamp(12);
}

}

extern "C" void kernel_launch(void* const* d_in, const int* in_sizes, int n_in, void* d_out, int out_size) {
    (void)in_sizes; (void)n_in; (void)out_size;
    static bool configured = false;
    if (!configured) {
        cudaFuncSetAttribute(mpnn_kernel, cudaFuncAttributeMaxDynamicSharedMemorySize, SM_TOTAL);
        configured = true;
    }
    mpnn_kernel<<<NB, NT, SM_TOTAL>>>(
        (const __nv_bfloat16*)d_in[0], (const __nv_bfloat16*)d_in[1], (const int*)d_in[2], (const int*)d_in[3],
        (const __nv_bfloat16*)d_in[4], (const __nv_bfloat16*)d_in[5], (const __nv_bfloat16*)d_in[6],
        (const __nv_bfloat16*)d_in[7], (__nv_bfloat16*)d_out);
}
```

```cpp
#include <cuda_runtime.h>
#include <cuda_bf16.h>
#include <stdint.h>

#define DEVI __device__ __forceinline__

namespace {
#define DELAY 1500
#define NTMA 4

constexpr int N_NODES = 12500;
constexpr int N_EDGES = 800000;
constexpr int NB = 132;
constexpr int NT = 768;
constexpr int NW = NT / 32;
constexpr int NPC = 95;
constexpr uint32_t OWN_M = 45210183u;
constexpr int QUADS = N_EDGES / 4;
constexpr int MAXN = 96;
constexpr int SLOTS = 6208;
constexpr int NODE_OFF = SLOTS * 4;
constexpr int STAGEB = SLOTS * 5;
constexpr int TAB_STRIDE = 192;
constexpr int LIST_CAP = 8192;
constexpr int S_STRIDE = 272;
constexpr int SLOW_ROUNDS = (QUADS + 2 * NT - 1) / (2 * NT);

constexpr int SM_STAGE = 0;
constexpr int SM_S = 0;
constexpr int SM_H = MAXN * S_STRIDE;
constexpr int SM_P = 31104;
constexpr int SM_W1 = 56320;
constexpr int SM_LIST = SM_W1;
constexpr int SM_W2 = SM_LIST + LIST_CAP * 4;
constexpr int SM_X = SM_W2;
constexpr int SM_Q = SM_W2 + 16384;
constexpr int SM_B1 = SM_Q + (MAXN + 1) * 256;
constexpr int SM_WE = SM_B1 + 256;
constexpr int SM_B2 = SM_WE + 256;
constexpr int SM_EP = SM_B2 + 128;
constexpr int SM_BASE2 = SM_EP + 16;
constexpr int SM_DEG = SM_BASE2 + 400;
constexpr int SM_BASE = SM_DEG + 384;
constexpr int SM_HIST = SM_BASE + 656;
constexpr int SM_HIST2 = SM_HIST + 640;
constexpr int SM_FLAG = SM_HIST2 + 384;
constexpr int SM_TOTAL = SM_FLAG + 208;

__device__ uint4 g_Pbuf[1 << 20];
__device__ uint4 g_rec[NB * STAGEB / 16];
__device__ uint32_t g_tab[NB * TAB_STRIDE];
__device__ uint4 g_epoch;
__device__ uint32_t g_pcount;
DEVI void stamp(int, int = 0) {}

DEVI uint32_t smem_u32(const void* p) { return (uint32_t)__cvta_generic_to_shared(p); }
DEVI void cp_async16(uint32_t dst, const void* src) {
    asm volatile("cp.async.cg.shared.global [%0],[%1],16;" ::"r"(dst), "l"(src) : "memory");
}
DEVI uint4 ldg_nc128(const void* p) {
    uint4 v;
    asm volatile("ld.global.nc.L1::no_allocate.v4.u32 {%0,%1,%2,%3},[%4];" : "=r"(v.x), "=r"(v.y), "=r"(v.z), "=r"(v.w) : "l"(p));
    return v;
}
DEVI uint2 ldg_nc64(const void* p) {
    uint2 v;
    asm volatile("ld.global.nc.L1::no_allocate.v2.u32 {%0,%1},[%2];" : "=r"(v.x), "=r"(v.y) : "l"(p));
    return v;
}
template <int OFF>
DEVI void ldg128p(uint4& v, const void* p, bool pred) {
    asm volatile("{.reg .pred p; setp.ne.u32 p,%6,0; @p ld.global.L1::no_allocate.v4.u32 {%0,%1,%2,%3},[%4+%5];}"
                 : "=r"(v.x), "=r"(v.y), "=r"(v.z), "=r"(v.w) : "l"(p), "n"(OFF), "r"((uint32_t)pred) : "memory");
}
template <int OFF>
DEVI void ldg64p(uint2& v, const void* p, bool pred) {
    asm volatile("{.reg .pred p; setp.ne.u32 p,%4,0; @p ld.global.L1::no_allocate.v2.u32 {%0,%1},[%2+%3];}"
                 : "=r"(v.x), "=r"(v.y) : "l"(p), "n"(OFF), "r"((uint32_t)pred) : "memory");
}
template <int OFF>
DEVI void ldg128a(uint4& v, const void* p) {
    asm volatile("ld.global.v4.u32 {%0,%1,%2,%3},[%4+%5];" : "=r"(v.x), "=r"(v.y), "=r"(v.z), "=r"(v.w) : "l"(p), "n"(OFF) : "memory");
}
template <int OFF>
DEVI void load_pair(uint32_t& r0, uint32_t& r1, uint32_t& nd, uint32_t& msk, const uint8_t* base, uint32_t e, uint32_t idx) {
    const uint32_t np = e >> 12, pair = (e & 0xfffu) + min(idx, np);
    msk = idx < np ? 0u : 0x7f7fu;
    asm volatile("ld.relaxed.gpu.global.v2.u32 {%0,%1},[%3+%5];\n"
                 "ld.relaxed.gpu.global.u16 %2,[%4+%6];"
                 : "=r"(r0), "=r"(r1), "=r"(nd) : "l"(base + pair * 8), "l"(base + pair * 2), "n"(OFF), "n"(OFF + NODE_OFF) : "memory");
}
DEVI uint32_t rank_slot(uint32_t a, uint32_t tab) {
    uint32_t r;
    asm volatile("{.reg .pred p; setp.ne.u32 p,%1,0x7f; @p atom.shared.add.u32 %0,[%2],4;}" : "=r"(r) : "r"(a), "r"(tab + a * 4) : "memory");
    return r;
}
DEVI void place_slot(uint32_t a, uint32_t tab, uint32_t rk, uint32_t rec) {
    asm volatile("{.reg .pred p; .reg .b32 d; setp.ne.u32 p,%0,0x7f; @p ld.shared.u32 d,[%1]; @p add.u32 d,d,%2; @p st.shared.u32 [d],%3;}"
                 ::"r"(a), "r"(tab + a * 4), "r"(rk), "r"(rec) : "memory");
}
DEVI uint4 lds128(uint32_t a) {
    uint4 v;
    asm volatile("ld.shared.v4.u32 {%0,%1,%2,%3},[%4];" : "=r"(v.x), "=r"(v.y), "=r"(v.z), "=r"(v.w) : "r"(a) : "memory");
    return v;
}
DEVI void sts128(uint32_t a, uint4 v) {
    asm volatile("st.shared.v4.u32 [%0],{%1,%2,%3,%4};" ::"r"(a), "r"(v.x), "r"(v.y), "r"(v.z), "r"(v.w) : "memory");
}
DEVI uint4 ldg_row(uint32_t lo, uint32_t hi) {
    uint4 v;
    asm volatile("{.reg .b64 ad; mov.b64 ad,{%4,%5}; ld.global.v4.u32 {%0,%1,%2,%3},[ad];}"
                 : "=r"(v.x), "=r"(v.y), "=r"(v.z), "=r"(v.w) : "r"(lo), "r"(hi));
    return v;
}
DEVI void ldsm4(uint32_t& r0, uint32_t& r1, uint32_t& r2, uint32_t& r3, uint32_t a) {
    asm volatile("ldmatrix.sync.aligned.m8n8.x4.shared.b16 {%0,%1,%2,%3},[%4];"
                 : "=r"(r0), "=r"(r1), "=r"(r2), "=r"(r3) : "r"(a) : "memory");
}
DEVI void ldsm4t(uint32_t& r0, uint32_t& r1, uint32_t& r2, uint32_t& r3, uint32_t a) {
    asm volatile("ldmatrix.sync.aligned.m8n8.x4.trans.shared.b16 {%0,%1,%2,%3},[%4];"
                 : "=r"(r0), "=r"(r1), "=r"(r2), "=r"(r3) : "r"(a) : "memory");
}
DEVI void mma_bf16(float (&c)[4], uint32_t a0, uint32_t a1, uint32_t a2, uint32_t a3, uint32_t b0, uint32_t b1) {
    asm volatile("mma.sync.aligned.m16n8k16.row.col.f32.bf16.bf16.f32 {%0,%1,%2,%3},{%4,%5,%6,%7},{%8,%9},{%0,%1,%2,%3};"
                 : "+f"(c[0]), "+f"(c[1]), "+f"(c[2]), "+f"(c[3])
                 : "r"(a0), "r"(a1), "r"(a2), "r"(a3), "r"(b0), "r"(b1));
}
template <int ACC>
DEVI void wgmma_n96(float (&d)[48], uint32_t a, uint32_t bm) {
    asm volatile("{.reg .pred p; .reg .b64 da,db; setp.ne.b32 p,%50,0; mov.b64 da,{%48,0x40000040}; mov.b64 db,{%49,0x40000040};\n"
                 "wgmma.mma_async.sync.aligned.m64n96k16.f32.bf16.bf16 "
                 "{%0,%1,%2,%3,%4,%5,%6,%7,%8,%9,%10,%11,%12,%13,%14,%15,%16,%17,%18,%19,%20,%21,%22,%23,%24,%25,%26,%27,%28,%29,%30,%31,%32,%33,%34,%35,%36,%37,%38,%39,%40,%41,%42,%43,%44,%45,%46,%47},"
                 "da,db,p,1,1,1,0;}\n"
                 : "+f"(d[0]), "+f"(d[1]), "+f"(d[2]), "+f"(d[3]), "+f"(d[4]), "+f"(d[5]), "+f"(d[6]), "+f"(d[7]), "+f"(d[8]), "+f"(d[9]), "+f"(d[10]), "+f"(d[11]), "+f"(d[12]), "+f"(d[13]), "+f"(d[14]), "+f"(d[15]), "+f"(d[16]), "+f"(d[17]), "+f"(d[18]), "+f"(d[19]), "+f"(d[20]), "+f"(d[21]), "+f"(d[22]), "+f"(d[23]), "+f"(d[24]), "+f"(d[25]), "+f"(d[26]), "+f"(d[27]), "+f"(d[28]), "+f"(d[29]), "+f"(d[30]), "+f"(d[31]), "+f"(d[32]), "+f"(d[33]), "+f"(d[34]), "+f"(d[35]), "+f"(d[36]), "+f"(d[37]), "+f"(d[38]), "+f"(d[39]), "+f"(d[40]), "+f"(d[41]), "+f"(d[42]), "+f"(d[43]), "+f"(d[44]), "+f"(d[45]), "+f"(d[46]), "+f"(d[47])
                 : "r"(a), "r"(bm), "n"(ACC));
}
DEVI uint32_t pack_bf16(float lo, float hi) {
    uint32_t r;
    asm("cvt.rn.bf16x2.f32 %0,%1,%2;" : "=r"(r) : "f"(hi), "f"(lo));
    return r;
}
DEVI float bf_lo(uint32_t v) { return __uint_as_float(v << 16); }
DEVI float bf_hi(uint32_t v) { return __uint_as_float(v & 0xffff0000u); }
DEVI __nv_bfloat162 as_bf2(uint32_t v) { return *reinterpret_cast<__nv_bfloat162*>(&v); }
DEVI uint32_t as_u32(__nv_bfloat162 v) { return *reinterpret_cast<uint32_t*>(&v); }
DEVI uint32_t tanh_bf2(uint32_t a) {
    uint32_t d;
    asm("tanh.approx.bf16x2 %0,%1;" : "=r"(d) : "r"(a));
    return d;
}
DEVI uint32_t half_bf2(uint32_t v) { return as_u32(__hmul2(as_bf2(v), as_bf2(0x3f003f00u))); }

DEVI void edge_pre(uint32_t rec, const uint4& p, const uint32_t (&w)[4], const uint32_t (&q)[4], __nv_bfloat162 (&u)[4]) {
    const __nv_bfloat162 e2 = __high2bfloat162(as_bf2(rec));
    const uint32_t pw[4] = {p.x, p.y, p.z, p.w};
#pragma unroll
    for (int i = 0; i < 4; i++) u[i] = __hadd2(__hfma2(e2, as_bf2(w[i]), as_bf2(q[i])), as_bf2(pw[i]));
}
DEVI __nv_bfloat162 act(__nv_bfloat162 u) { return __hfma2(u, as_bf2(tanh_bf2(as_u32(u))), u); }

DEVI void wait_p(const uint8_t* smem) {
    const uint32_t epoch = *reinterpret_cast<const volatile uint32_t*>(smem + SM_EP) + 1;
    uint32_t v;
    int spins = 0;
    do {
        asm volatile("ld.acquire.gpu.global.u32 %0,[%1];" : "=r"(v) : "l"(&g_pcount) : "memory");
        if (++spins > (1 << 22)) __trap();
    } while ((int)(v - epoch * NB) < 0);
    if (blockIdx.x == 0) g_epoch.x = epoch;
}
DEVI void store_partial(uint8_t* smem, int stream, int l16, const float (&acc)[8], uint32_t f) {
    float4* hp = reinterpret_cast<float4*>(smem + SM_H + stream * 512 + l16 * 16);
    hp[0] = make_float4(acc[0], acc[1], acc[2], acc[3]);
    hp[16] = make_float4(acc[4], acc[5], acc[6], acc[7]);
    __threadfence_block();
    __syncwarp(0xffffu << ((stream & 1) * 16));
    if (l16 == 0) *reinterpret_cast<volatile uint32_t*>(smem + SM_FLAG + stream * 4) = f;
}

template <bool SLOW>
DEVI bool sort_and_stream(uint8_t* smem, int& tid, const uint32_t (&rw)[9][2], const uint32_t (&nd)[9],
                          uint32_t plo, uint32_t phi, uint32_t dummy, int nn, bool first, bool tail, bool ovf,
                          float (&c)[2][4]) {
    const uint32_t sb = smem_u32(smem);
    int lane = tid & 31, warp = tid >> 5, l16 = lane & 15;
    uint32_t* hist2 = reinterpret_cast<uint32_t*>(smem + SM_HIST2);
    uint32_t* base2 = reinterpret_cast<uint32_t*>(smem + SM_BASE2);
    volatile uint32_t* flag = reinterpret_cast<volatile uint32_t*>(smem + SM_FLAG);
    uint32_t* sdeg = reinterpret_cast<uint32_t*>(smem + SM_DEG);
    constexpr int NMAIN = SLOW ? 4 : 6;
    uint32_t rk[9][2];
#pragma unroll
    for (int i = 0; i < NMAIN; i++) {
        rk[i][0] = rank_slot(nd[i] & 0x7fu, sb + SM_HIST2);
        rk[i][1] = rank_slot((nd[i] >> 8) & 0x7fu, sb + SM_HIST2);
    }
    if (!SLOW) {
#pragma unroll
        for (int i = 6; i < 9; i++) rk[i][0] = rk[i][1] = 0;
        if (tail) {
#pragma unroll
            for (int i = 6; i < 9; i++) {
                rk[i][0] = rank_slot(nd[i] & 0x7fu, sb + SM_HIST2);
                rk[i][1] = rank_slot((nd[i] >> 8) & 0x7fu, sb + SM_HIST2);
            }
        }
    }
    ovf = __syncthreads_or(ovf);
    stamp(6);
    const uint32_t lbeg = sb + SM_LIST, lend = lbeg + LIST_CAP * 4 - 64;
    if (warp == 0) {
        uint32_t cn[3], pg[3], sum = 0;
#pragma unroll
        for (int i = 0; i < 3; i++) {
            cn[i] = hist2[lane * 3 + i];
            pg[i] = (lane * 3 + i < nn) ? max((cn[i] + 12) & ~15u, 16u) : 0u;
            sum += pg[i];
        }
        uint32_t inc = sum;
#pragma unroll
        for (int o = 1; o < 32; o <<= 1) {
            const uint32_t v = __shfl_up_sync(0xffffffffu, inc, o);
            if (lane >= o) inc += v;
        }
        const uint32_t tot = lbeg + __shfl_sync(0xffffffffu, inc, 31);
        const bool fits = !ovf && tot <= lend;
        uint32_t run = lbeg + inc - sum;
        const uint4 d4 = make_uint4(dummy, dummy, dummy, dummy);
#pragma unroll
        for (int i = 0; i < 3; i++) {
            base2[lane * 3 + i] = run;
            run += pg[i];
            if (fits && pg[i]) sts128(run - 16, d4);
            sdeg[lane * 3 + i] = cn[i];
            if (SLOW && lane < 16) flag[lane * 3 + i] = 0;
            hist2[lane * 3 + i] = 0;
        }
        if (lane < 4) {
            base2[96 + lane] = tot;
            if (fits) sts128(tot + lane * 16, d4);
        }
        if (!SLOW) asm volatile("bar.arrive 2,64;" ::: "memory");
    }
    if (!SLOW && warp == 1) {
        asm volatile("bar.arrive 3,%0;" ::"n"(NT) : "memory");
        if (lane == 0) asm volatile("red.release.gpu.global.add.u32 [%0],1;" ::"l"(&g_pcount) : "memory");
        asm volatile("bar.sync 2,64;" ::: "memory");
    } else {
        asm volatile("bar.sync 3,%0;" ::"n"(NT) : "memory");
    }
    stamp(7);
    const uint32_t tot = base2[96];
    if (!SLOW && (ovf || tot > lend)) {
        if (tid == 0) wait_p(smem);
        __syncthreads();
        return false;
    }
#pragma unroll
    for (int i = 0; i < NMAIN; i++) {
        place_slot(nd[i] & 0x7fu, sb + SM_BASE2, rk[i][0], rw[i][0]);
        place_slot((nd[i] >> 8) & 0x7fu, sb + SM_BASE2, rk[i][1], rw[i][1]);
    }
    if (tail) {
#pragma unroll
        for (int i = 6; i < 9; i++) {
            place_slot(nd[i] & 0x7fu, sb + SM_BASE2, rk[i][0], rw[i][0]);
            place_slot((nd[i] >> 8) & 0x7fu, sb + SM_BASE2, rk[i][1], rw[i][1]);
        }
    }
    const uint32_t T2 = (tot - lbeg + 16) >> 5;
    const uint32_t per = T2 / NW, rem = T2 - per * NW;
    const int cnt = per + ((uint32_t)warp < rem);
    const uint32_t rs0 = lbeg + 32 * (warp * per + min((uint32_t)warp, rem)), rs1 = rs0 + 16 * cnt;
    int node;
    {
        int c0 = -1, c1 = -1;
#pragma unroll
        for (int i = 0; i < 3; i++) {
            const uint32_t gb = base2[lane + 32 * i];
            c0 += __popc(__ballot_sync(0xffffffffu, gb <= rs0));
            c1 += __popc(__ballot_sync(0xffffffffu, gb <= rs1));
        }
        node = lane < 16 ? c0 : c1;
    }
    uint32_t ri = lane < 16 ? rs0 : rs1;
    int dn = base2[node + 1] - ri;
    uint32_t qv[4], wv[4];
    {
        const uint4 w = lds128(sb + SM_WE + l16 * 16);
        wv[0] = half_bf2(w.x); wv[1] = half_bf2(w.y); wv[2] = half_bf2(w.z); wv[3] = half_bf2(w.w);
        const uint4 v = lds128(sb + SM_Q + node * 256 + ((l16 ^ (node & 7)) << 4));
        qv[0] = v.x; qv[1] = v.y; qv[2] = v.z; qv[3] = v.w;
    }
    asm volatile("cp.async.wait_group 0;" ::: "memory");
    if (!SLOW && tid == NT - 32) wait_p(smem);
    __syncthreads();
    stamp(8);

    float acc[8];
#pragma unroll
    for (int i = 0; i < 8; i++) acc[i] = 0.f;
    uint4 rA = lds128(ri), rB = lds128(ri + 16), A[4];
#define LOAD_GROUP(buf, r)                                         \
    {                                                              \
        buf[0] = ldg_row(__byte_perm(r.x, plo, 0x7104), phi);      \
        buf[1] = ldg_row(__byte_perm(r.y, plo, 0x7104), phi);      \
        buf[2] = ldg_row(__byte_perm(r.z, plo, 0x7104), phi);      \
        buf[3] = ldg_row(__byte_perm(r.w, plo, 0x7104), phi);      \
    }
#define COMPUTE_GROUP(buf, r, rn, off, MORE)                                                     \
    {                                                                                      \
        __nv_bfloat162 s0[4], s1[4], s2[4], s3[4];                                         \
        edge_pre(r.x, buf[0], wv, qv, s0);                                                 \
        edge_pre(r.y, buf[1], wv, qv, s1);                                                 \
        edge_pre(r.z, buf[2], wv, qv, s2);                                                 \
        edge_pre(r.w, buf[3], wv, qv, s3);                                                 \
        if (MORE) {                                                                        \
            LOAD_GROUP(buf, rn);                                                           \
            r = lds128(ri + off + 16);                                                     \
        }                                                                                  \
        _Pragma("unroll") for (int i = 0; i < 4; i++) {                                    \
            const uint32_t v = as_u32(__hadd2(__hadd2(act(s0[i]), act(s1[i])), __hadd2(act(s2[i]), act(s3[i])))); \
            acc[2 * i] += bf_lo(v);                                                        \
            acc[2 * i + 1] += bf_hi(v);                                                    \
        }                                                                                  \
        if (dn == off) {     \
            int tt;                                                                        \
            asm volatile("mov.u32 %0,%1;" : "=r"(tt) : "r"(tid));                          \
            if (node < 0) {                                                                \
                store_partial(smem, tt >> 4, tt & 15, acc, 1u);                            \
                node = ~node;                                                              \
            } else {                                                                       \
                sts128(sb + SM_S + node * S_STRIDE + (tt & 15) * 16,                       \
                       make_uint4(pack_bf16(acc[0], acc[1]), pack_bf16(acc[2], acc[3]),    \
                                  pack_bf16(acc[4], acc[5]), pack_bf16(acc[6], acc[7])));  \
            }                                                                              \
            node++;                                                                        \
            dn = base2[node + 1] - ri;                                                     \
            const uint4 v = lds128(sb + SM_Q + node * 256 + (((tt & 15) ^ (node & 7)) << 4)); \
            qv[0] = v.x; qv[1] = v.y; qv[2] = v.z; qv[3] = v.w;                            \
            _Pragma("unroll") for (int i = 0; i < 8; i++) acc[i] = 0.f;                    \
        }                                                                                  \
    }
    if (base2[node] != ri) node = ~node;
    LOAD_GROUP(A, rA);
    int left = cnt;
    if (SLOW) {
#pragma unroll 1
        for (; left > 0; left--) {
            COMPUTE_GROUP(A, rA, rA, 16, false);
            ri += 16;
            dn -= 16;
            rA = lds128(ri);
            LOAD_GROUP(A, rA);
        }
    } else {
#pragma unroll 1
        while (left >= 2) {
            COMPUTE_GROUP(A, rA, rB, 16, true);
            COMPUTE_GROUP(A, rB, rA, 32, true);
            ri += 32;
            dn -= 32;
            left -= 2;
        }
        if (left) {
            COMPUTE_GROUP(A, rA, rA, 16, false);
            ri += 16;
        }
    }
    stamp(9);
    asm volatile("" : "+r"(tid));
    lane = tid & 31; warp = tid >> 5; l16 = lane & 15;
    if (node < 0) store_partial(smem, tid >> 4, l16, acc, 2u);
    __syncwarp();
    if ((uint32_t)node < (uint32_t)min(NPC, N_NODES - (int)blockIdx.x * NPC) && base2[node] < ri) {
        uint32_t f;
        int st = tid >> 4;
        do {
            st++;
            int spins = 0;
            while ((f = flag[st]) == 0) {
                if (++spins > (1 << 24)) __trap();
            }
            __threadfence_block();
            const float4* hp = reinterpret_cast<const float4*>(smem + SM_H + st * 512 + l16 * 16);
            const float4 u0 = hp[0], u1 = hp[16];
            acc[0] += u0.x; acc[1] += u0.y; acc[2] += u0.z; acc[3] += u0.w;
            acc[4] += u1.x; acc[5] += u1.y; acc[6] += u1.z; acc[7] += u1.w;
        } while (f == 2u);
        sts128(sb + SM_S + node * S_STRIDE + l16 * 16,
               make_uint4(pack_bf16(acc[0], acc[1]), pack_bf16(acc[2], acc[3]), pack_bf16(acc[4], acc[5]), pack_bf16(acc[6], acc[7])));
    }
    __syncwarp();
    const int mt = warp >> 2, nq = warp & 3;
    uint32_t wf[8][4];
    const uint32_t wa = sb + SM_W2 + l16 * 128 + (((nq * 2 + (lane >> 4)) ^ (lane & 7)) << 4);
#pragma unroll
    for (int s = 0; s < 8; s++) ldsm4t(wf[s][0], wf[s][1], wf[s][2], wf[s][3], wa + s * 2048);
    {
        const float d0 = 0.25f * (float)sdeg[mt * 16 + (lane >> 2)], d1 = 0.25f * (float)sdeg[mt * 16 + 8 + (lane >> 2)];
#pragma unroll
        for (int j = 0; j < 2; j++) {
            const uint32_t bb = reinterpret_cast<const uint32_t*>(smem + SM_B2)[nq * 8 + j * 4 + (lane & 3)];
            if (first) c[j][0] = c[j][1] = c[j][2] = c[j][3] = 0.f;
            c[j][0] += d0 * bf_lo(bb); c[j][1] += d0 * bf_hi(bb);
            c[j][2] += d1 * bf_lo(bb); c[j][3] += d1 * bf_hi(bb);
        }
    }
    const uint32_t sa = sb + SM_S + (mt * 16 + l16) * S_STRIDE + (lane >> 4) * 16;
    __syncthreads();
    stamp(10);
#pragma unroll
    for (int s = 0; s < 8; s++) {
        uint32_t a0, a1, a2, a3;
        ldsm4(a0, a1, a2, a3, sa + s * 32);
        mma_bf16(c[0], a0, a1, a2, a3, wf[s][0], wf[s][1]);
        mma_bf16(c[1], a0, a1, a2, a3, wf[s][2], wf[s][3]);
    }
    return true;
}

DEVI void store_out(__nv_bfloat16* out, const float (&c)[2][4], int tid) {
    const int n0 = blockIdx.x * NPC, nn = min(NPC, N_NODES - n0);
    const int row0 = (tid >> 7) * 16 + ((tid & 31) >> 2);
    uint32_t* o = reinterpret_cast<uint32_t*>(out) + (n0 + row0) * 32 + ((tid >> 5) & 3) * 8 + (tid & 3);
#pragma unroll
    for (int j = 0; j < 2; j++) {
        if (row0 < nn) o[j * 4] = pack_bf16(c[j][0], c[j][1]);
        if (row0 + 8 < nn) o[j * 4 + 8 * 32] = pack_bf16(c[j][2], c[j][3]);
    }
}

__device__ __noinline__ void slow_path(uint8_t* smem, const __nv_bfloat16* ea, const int* src, const int* dst,
                                       __nv_bfloat16* out, uint64_t pbase) {
    int tid = threadIdx.x;
    const int l16 = tid & 15, n0 = blockIdx.x * NPC, nn = min(NPC, N_NODES - n0);
    const uint32_t rowc = ((uint32_t)pbase >> 8) & 0xc000u;
    const uint32_t plo = ((uint32_t)pbase & 0xff000000u) | (l16 * 16), phi = (uint32_t)(pbase >> 32);
    uint32_t rw[9][2], nd[9];
    float c[2][4];
#pragma unroll 1
    for (int round = 0; round < SLOW_ROUNDS; round++) {
#pragma unroll
        for (int h = 0; h < 2; h++) {
            const int q = (round * 2 + h) * NT + tid;
            const int qq = min(q, QUADS - 1);
            const uint4 d4 = ldg_nc128(reinterpret_cast<const uint4*>(dst) + qq);
            const uint4 s4 = ldg_nc128(reinterpret_cast<const uint4*>(src) + qq);
            const uint2 e4 = ldg_nc64(reinterpret_cast<const uint2*>(ea) + qq);
            rw[2 * h][0] = __byte_perm(s4.x | rowc, e4.x, 0x5410);
            rw[2 * h][1] = __byte_perm(s4.y | rowc, e4.x, 0x7610);
            rw[2 * h + 1][0] = __byte_perm(s4.z | rowc, e4.y, 0x5410);
            rw[2 * h + 1][1] = __byte_perm(s4.w | rowc, e4.y, 0x7610);
            const uint32_t lim = q < QUADS ? NPC : 0;
            const uint32_t a0 = d4.x - n0, a1 = d4.y - n0, a2 = d4.z - n0, a3 = d4.w - n0;
            nd[2 * h] = (a0 < lim ? a0 : 0x7fu) | ((a1 < lim ? a1 : 0x7fu) << 8);
            nd[2 * h + 1] = (a2 < lim ? a2 : 0x7fu) | ((a3 < lim ? a3 : 0x7fu) << 8);
        }
        sort_and_stream<true>(smem, tid, rw, nd, plo, phi, rowc | N_NODES, nn, round == 0, false, false, c);
    }
    store_out(out, c, tid);
}

__global__ void __launch_bounds__(NT, 1)
mpnn_kernel(const __nv_bfloat16* __restrict__ x, const __nv_bfloat16* __restrict__ ea,
            const int* __restrict__ src, const int* __restrict__ dst,
            const __nv_bfloat16* __restrict__ w1, const __nv_bfloat16* __restrict__ b1,
            const __nv_bfloat16* __restrict__ w2, const __nv_bfloat16* __restrict__ b2,
            __nv_bfloat16* __restrict__ out) {
    extern __shared__ __align__(1024) uint8_t smem[];
    const uint32_t sb = smem_u32(smem);
    int tid;
    asm volatile("shfl.sync.bfly.b32 %0,%1,0,31,0xffffffff;" : "=r"(tid) : "r"(threadIdx.x));
    const int lane = tid & 31, warp = tid >> 5;
    const int b = blockIdx.x;
    const int g = lane >> 2;
    const int n0 = b * NPC;
    const int nn = min(NPC, N_NODES - n0);
    uint32_t* hist = reinterpret_cast<uint32_t*>(smem + SM_HIST);
    stamp(0);

    const int q0 = b * 1515 + min(b, 20) + tid;
    const bool has2 = tid < 1515 - NT + (b < 20);
    uint4 vd[2], vs[2];
    uint2 ve[2];
    ldg128p<0>(vd[0], reinterpret_cast<const uint4*>(dst) + q0, true);
    ldg128p<NT * 16>(vd[1], reinterpret_cast<const uint4*>(dst) + q0, has2);
    if (tid >= NT - 64) {
        const int i = tid - (NT - 64);
        const uint8_t* p = i < 16 ? reinterpret_cast<const uint8_t*>(b1) + i * 16
                         : i < 32 ? reinterpret_cast<const uint8_t*>(w1) + 32768 - 256 + i * 16
                         : i < 40 ? reinterpret_cast<const uint8_t*>(b2) - 512 + i * 16
                                  : reinterpret_cast<const uint8_t*>(&g_epoch);
        if (i <= 40) cp_async16(sb + SM_B1 + i * 16, p);
    }
    asm volatile("cp.async.commit_group;" ::: "memory");
    if (tid < (SM_TOTAL - SM_HIST) / 4) hist[tid] = 0;
    __syncthreads();
    ldg128p<0>(vs[0], reinterpret_cast<const uint4*>(src) + q0, true);
    ldg64p<0>(ve[0], reinterpret_cast<const uint2*>(ea) + q0, true);
    ldg128p<NT * 16>(vs[1], reinterpret_cast<const uint4*>(src) + q0, has2);
    ldg64p<NT * 8>(ve[1], reinterpret_cast<const uint2*>(ea) + q0, has2);
    asm volatile("bar.sync 1,%0;" ::"n"(NT) : "memory");

    const uint32_t* dd = reinterpret_cast<const uint32_t*>(vd);
    uint32_t rk0[8];
#pragma unroll
    for (int i = 0; i < 8; i++) {
        asm volatile("{.reg .pred p; setp.ne.u32 p,%2,0; @p atom.shared.add.u32 %0,[%1],1;}"
                     : "=r"(rk0[i]) : "r"(sb + SM_HIST + __umulhi(dd[i], OWN_M) * 4), "r"((uint32_t)(i < 4 || has2)) : "memory");
    }
    cp_async16(sb + SM_X + (tid >> 3) * 128 + (((tid ^ (tid >> 3)) & 7) << 4),
               reinterpret_cast<const uint8_t*>(x) + min(n0 * 8 + tid, N_NODES * 8 - 1) * 16);
#pragma unroll
    for (int k = 0; k < 3; k++) {
        if (k < 2 || tid < 2048 - 2 * NT)
            cp_async16(sb + SM_W1 + k * 6144 + (tid & 8) * 2048 + (tid >> 4) * 128 + (((tid ^ (tid >> 4)) & 7) << 4),
                       reinterpret_cast<const uint8_t*>(w1) + (tid + k * NT) * 16);
    }
    asm volatile("cp.async.commit_group;" ::: "memory");
    asm volatile("cp.async.wait_group 1;" ::: "memory");
    __syncthreads();
    stamp(1);
    const uint32_t epoch = *reinterpret_cast<const uint32_t*>(smem + SM_EP) + 1;
    const uint32_t par = epoch & 1;
    uint32_t fill = 0x7f7f7f7fu | (par * 0x80808080u);
    asm volatile("" : "+r"(fill));
    uint32_t* base = reinterpret_cast<uint32_t*>(smem + SM_BASE);
    uint64_t pbase = (reinterpret_cast<uint64_t>(g_Pbuf) + 0x3fffffu) & ~(uint64_t)0x3fffffu;
    if ((((uint32_t)pbase >> 23) & 1) != par) pbase += 0x800000u;
    const uint32_t rowc = ((uint32_t)pbase >> 8) & 0xc000u;
    if (warp == 16) {
        uint32_t cn[5], sum = 0;
#pragma unroll
        for (int i = 0; i < 5; i++) { cn[i] = (hist[lane * 5 + i] + 1) & ~1u; sum += cn[i]; }
        uint32_t inc = sum;
#pragma unroll
        for (int o = 1; o < 32; o <<= 1) {
            const uint32_t v = __shfl_up_sync(0xffffffffu, inc, o);
            if (lane >= o) inc += v;
        }
        uint32_t run = inc - sum;
#pragma unroll
        for (int i = 0; i < 5; i++) {
            base[lane * 5 + i] = run;
            run += cn[i];
            if (cn[i]) smem[SM_STAGE + NODE_OFF + run - 1] = (uint8_t)fill;
        }
    } else if (warp == 17 || warp == 18) {
        const int i = tid - 17 * 32;
        if (i < 50) sts128(sb + SM_STAGE + (i < 40 ? 6048 * 4 + i * 16 : NODE_OFF + 6048 - 640 + i * 16), make_uint4(fill, fill, fill, fill));
    } else if (warp == 19 && b == 0 && lane < 16) {
        asm volatile("st.global.v4.u32 [%0],{%1,%1,%1,%1};" ::"l"(pbase + N_NODES * 256 + lane * 16), "r"(0xff00ff00u) : "memory");
    }
    __syncthreads();
    stamp(2);
    if (warp == 18) {
        uint32_t en[5];
#pragma unroll
        for (int i = 0; i < 5; i++) {
            const uint32_t o = base[lane + 32 * i], e = base[lane + 32 * i + 1];
            en[i] = (o >> 1) | ((e - o) << 11) | (epoch << 24);
        }
        uint32_t* tp = &g_tab[lane * TAB_STRIDE + (b % NW) * 8 + b / NW];
#pragma unroll
        for (int i = 0; i < 5; i++) {
            if (lane + 32 * i < NB)
                asm volatile("st.relaxed.gpu.global.u32 [%0],%1;" ::"l"(tp + 32 * i * TAB_STRIDE), "r"(en[i]) : "memory");
        }
    }
    {
        const uint32_t* ss = reinterpret_cast<const uint32_t*>(vs);
        const uint32_t* ee = reinterpret_cast<const uint32_t*>(ve);
#pragma unroll
        for (int h = 0; h < 2; h++) {
            if (h == 0 || has2) {
#pragma unroll
                for (int i = h * 4; i < h * 4 + 4; i++) {
                    const uint32_t own = __umulhi(dd[i], OWN_M);
                    const uint32_t pos = base[own] + rk0[i];
                    smem[SM_STAGE + NODE_OFF + pos] = (uint8_t)(dd[i] + (par << 7) - own * NPC);
                    reinterpret_cast<uint32_t*>(smem + SM_STAGE)[pos] = __byte_perm(ss[i] | rowc, ee[i >> 1], (i & 1) ? 0x7610 : 0x5410);
                }
            }
        }
        asm volatile("cp.async.wait_group 0;" ::: "memory");
        __syncthreads();
        stamp(3);
        if (warp < 16) asm volatile("fence.proxy.async.shared::cta;" ::: "memory");

    }
    uint32_t ent = epoch << 24;
    const uint32_t* tabp = &g_tab[b * TAB_STRIDE + warp * 8 + lane];
    const uint32_t tst = clock();
    if (warp >= 16) {
        if (NTMA && tid == 16 * 32) {
            asm volatile("fence.proxy.async.shared::cta;" ::: "memory");
            asm volatile("cp.async.bulk.global.shared::cta.bulk_group [%0],[%1],%2;" ::"l"(g_rec + b * (STAGEB / 16)), "r"(sb + SM_STAGE), "n"(NTMA * 4096) : "memory");
            asm volatile("cp.async.bulk.commit_group;" ::: "memory");
        }
        __syncwarp();
        uint4 v[8];
#pragma unroll
        for (int k = NTMA; k < 8; k++) v[k] = lds128(sb + SM_STAGE + (tid - 512) * 16 + k * 4096);
#pragma unroll
        for (int k = NTMA; k < 8; k++) if (k < 7 || tid - 512 < STAGEB / 16 - 7 * 256) g_rec[b * (STAGEB / 16) + tid - 512 + k * 256] = v[k];
    }
    if (warp + NW * lane < NB) asm volatile("ld.relaxed.gpu.global.u32 %0,[%1];" : "=r"(ent) : "l"(tabp) : "memory");
    if (warp < 16) {
        const int wg = __shfl_sync(0xffffffffu, warp >> 2, 0);
        const uint32_t xa = ((sb + SM_X) >> 4) | 0x10000u, wa = ((sb + SM_W1 + (wg >> 1) * 8192 + (wg & 1) * 16384) >> 4) | 0x10000u;
        float d[48];
        asm volatile("wgmma.fence.sync.aligned;" ::: "memory");
        wgmma_n96<0>(d, wa, xa);
        wgmma_n96<1>(d, wa + 128, xa + 2);
        wgmma_n96<1>(d, wa + 256, xa + 4);
        wgmma_n96<1>(d, wa + 384, xa + 6);
        asm volatile("wgmma.commit_group.sync.aligned;" ::: "memory");
        const __nv_bfloat16* bp = reinterpret_cast<const __nv_bfloat16*>(smem + SM_B1) + (warp & 7) * 16 + g;
        const float hb = warp < 8 ? 0.f : 0.5f, bb0 = hb * __bfloat162float(bp[0]), bb1 = hb * __bfloat162float(bp[8]);
        const uint32_t qa = sb + (warp < 8 ? SM_P : SM_Q) + ((lane >> 4) * 8 + (lane & 7)) * 256 +
                            ((((warp & 7) * 2 + ((lane >> 3) & 1)) ^ (lane & 7)) << 4);
        asm volatile("wgmma.wait_group.sync.aligned 0;" ::: "memory");
#pragma unroll
        for (int j = 0; j < 6; j++) {
            const float* dj = d + j * 8;
            asm volatile("stmatrix.sync.aligned.m8n8.x4.trans.shared.b16 [%0],{%1,%2,%3,%4};" ::"r"(qa + j * 4096),
                         "r"(pack_bf16(fmaf(dj[0], 0.5f, bb0), fmaf(dj[1], 0.5f, bb0))), "r"(pack_bf16(fmaf(dj[2], 0.5f, bb1), fmaf(dj[3], 0.5f, bb1))),
                         "r"(pack_bf16(fmaf(dj[4], 0.5f, bb0), fmaf(dj[5], 0.5f, bb0))), "r"(pack_bf16(fmaf(dj[6], 0.5f, bb1), fmaf(dj[7], 0.5f, bb1))) : "memory");
        }
    }
    if (tid == 16 * 32) {
        if (NTMA) asm volatile("cp.async.bulk.wait_group.read 0;" ::: "memory");
        while ((uint32_t)clock() - tst < DELAY) {}
    }
    __syncthreads();
    if (warp < 16) {
#pragma unroll
        for (int k = 0; k < 2; k++) {
            const int pos = (tid >> 3) + 64 * k, ck = tid & 7;
            cp_async16(sb + SM_W2 + pos * 128 + ((ck ^ (pos & 7)) << 4), reinterpret_cast<const uint8_t*>(w2) + pos * 128 + ck * 16);
        }
        asm volatile("cp.async.commit_group;" ::: "memory");
    }
    __syncwarp();
    const int l16 = lane & 15;
    const uint32_t plo = ((uint32_t)pbase & 0xff000000u) | (l16 * 16), phi = (uint32_t)(pbase >> 32);
    const uint32_t dummy = rowc | N_NODES;
    stamp(4);

    uint32_t rw[9][2], nd[9];
    bool tail, ovf;
    {
        {
            int spins = 0;
            while ((ent >> 24) != (epoch & 0xffu)) {
                asm volatile("ld.relaxed.gpu.global.u32 %0,[%1];" : "=r"(ent) : "l"(tabp) : "memory");
                if (++spins > (1 << 22)) __trap();
            }
            ent &= 0xffffffu;
        }
        __syncwarp();
        stamp(13);
        tail = __any_sync(0xffffffffu, ent >= (33u << 12));
        ovf = ent >= (49u << 12);
        const uint8_t* ra = reinterpret_cast<const uint8_t*>(g_rec) + warp * STAGEB;
        asm volatile("" : "+l"(ra));
        int spins = 0;
        bool bad;
        do {
            constexpr int W = NW * STAGEB;
            uint32_t mk[9];
            load_pair<0 * W>(rw[0][0], rw[0][1], nd[0], mk[0], ra, __shfl_sync(0xffffffffu, ent, 0), lane);
            load_pair<1 * W>(rw[1][0], rw[1][1], nd[1], mk[1], ra, __shfl_sync(0xffffffffu, ent, 1), lane);
            load_pair<2 * W>(rw[2][0], rw[2][1], nd[2], mk[2], ra, __shfl_sync(0xffffffffu, ent, 2), lane);
            load_pair<3 * W>(rw[3][0], rw[3][1], nd[3], mk[3], ra, __shfl_sync(0xffffffffu, ent, 3), lane);
            load_pair<4 * W>(rw[4][0], rw[4][1], nd[4], mk[4], ra, __shfl_sync(0xffffffffu, ent, 4), lane);
            load_pair<0>(rw[5][0], rw[5][1], nd[5], mk[5], ra + (warp < NB - 5 * NW ? 5 * W : 0), __shfl_sync(0xffffffffu, ent, 5), lane);
            uint32_t m = 0;
            if (tail) {
                const uint8_t* rb = ra + (lane >> 4) * W;
                load_pair<0 * W>(rw[6][0], rw[6][1], nd[6], mk[6], rb, __shfl_sync(0xffffffffu, ent, 0 + (lane >> 4)), l16 + 32);
                load_pair<2 * W>(rw[7][0], rw[7][1], nd[7], mk[7], rb, __shfl_sync(0xffffffffu, ent, 2 + (lane >> 4)), l16 + 32);
                load_pair<4 * W>(rw[8][0], rw[8][1], nd[8], mk[8], warp < NB - 5 * NW ? rb : ra, __shfl_sync(0xffffffffu, ent, 4 + (lane >> 4)), l16 + 32);
#pragma unroll
                for (int i = 6; i < 9; i++) { m |= (rw[i][0] ^ fill) | (nd[i] ^ fill); nd[i] |= mk[i]; }
            } else {
#pragma unroll
                for (int i = 6; i < 9; i++) rw[i][0] = rw[i][1] = nd[i] = 0;
            }
#pragma unroll
            for (int i = 0; i < 6; i++) { m |= (rw[i][0] ^ fill) | (nd[i] ^ fill); nd[i] |= mk[i]; }
            bad = __any_sync(0xffffffffu, m & 0x8000u);
            if (spins == 0) stamp(11);
            if (++spins > (1 << 20)) __trap();
        } while (bad);
    }
            {
#pragma unroll
                for (int k = 0; k < 2; k++) {
                    const int row = (tid >> 4) + 48 * k;
                    const uint4 v = lds128(sb + SM_P + row * 256 + ((l16 ^ (row & 7)) << 4));
                    if (row < nn) asm volatile("st.global.v4.u32 [%0],{%1,%2,%3,%4};" ::"l"(pbase + (n0 * 16 + tid + k * NT) * 16), "r"(v.x), "r"(v.y), "r"(v.z), "r"(v.w) : "memory");
                }
            }
    stamp(5);
    float c[2][4];
    if (!sort_and_stream<false>(smem, tid, rw, nd, plo, phi, dummy, nn, true, tail, ovf, c)) {
        slow_path(smem, ea, src, dst, out, pbase);
        return;
    }
    store_out(out, c, tid);
    stamp(12);
}

}

extern "C" void kernel_launch(void* const* d_in, const int* in_sizes, int n_in, void* d_out, int out_size) {
    (void)in_sizes; (void)n_in; (void)out_size;
    static bool configured = false;
    if (!configured) {
        cudaFuncSetAttribute(mpnn_kernel, cudaFuncAttributeMaxDynamicSharedMemorySize, SM_TOTAL);
        configured = true;
    }
    mpnn_kernel<<<NB, NT, SM_TOTAL>>>(
        (const __nv_bfloat16*)d_in[0], (const __nv_bfloat16*)d_in[1], (const int*)d_in[2], (const int*)d_in[3],
        (const __nv_bfloat16*)d_in[4], (const __nv_bfloat16*)d_in[5], (const __nv_bfloat16*)d_in[6],
        (const __nv_bfloat16*)d_in[7], (__nv_bfloat16*)d_out);
}
```

```cpp
#include <cuda_runtime.h>
#include <cuda_bf16.h>
#include <stdint.h>

#define DEVI __device__ __forceinline__

namespace {

constexpr int N_NODES = 12500;
constexpr int N_EDGES = 800000;
constexpr int NB = 132;
constexpr int NT = 768;
constexpr int NW = NT / 32;
constexpr int NPC = 95;
constexpr uint32_t OWN_M = 45210183u;
constexpr int QUADS = N_EDGES / 4;
constexpr int MAXN = 96;
constexpr int SLOTS = 6208;
constexpr int NODE_OFF = SLOTS * 4;
constexpr int STAGEB = SLOTS * 5;
constexpr int TAB_STRIDE = 192;
constexpr int LIST_CAP = 8192;
constexpr int S_STRIDE = 272;
constexpr int SLOW_ROUNDS = (QUADS + 2 * NT - 1) / (2 * NT);

constexpr int SM_STAGE = 0;
constexpr int SM_S = 0;
constexpr int SM_H = MAXN * S_STRIDE;
constexpr int SM_P = 31104;
constexpr int SM_W1 = 56320;
constexpr int SM_LIST = SM_W1;
constexpr int SM_W2 = SM_LIST + LIST_CAP * 4;
constexpr int SM_X = SM_W2;
constexpr int SM_Q = SM_W2 + 16384;
constexpr int SM_B1 = SM_Q + (MAXN + 1) * 256;
constexpr int SM_WE = SM_B1 + 256;
constexpr int SM_B2 = SM_WE + 256;
constexpr int SM_EP = SM_B2 + 128;
constexpr int SM_BASE2 = SM_EP + 16;
constexpr int SM_DEG = SM_BASE2 + 400;
constexpr int SM_BASE = SM_DEG + 384;
constexpr int SM_B16 = SM_BASE + 336;
constexpr int SM_HIST = SM_BASE + 656;
constexpr int SM_HIST2 = SM_HIST + 640;
constexpr int SM_FLAG = SM_HIST2 + 384;
constexpr int SM_TOTAL = SM_FLAG + 208;

__device__ uint4 g_Pbuf[1 << 20];
__device__ uint4 g_rec[NB * STAGEB / 16];
__device__ uint32_t g_tab[NB * TAB_STRIDE];
__device__ uint4 g_epoch;
__device__ uint32_t g_pcount;
DEVI void stamp(int, int = 0) {}

DEVI uint32_t smem_u32(const void* p) { return (uint32_t)__cvta_generic_to_shared(p); }
DEVI void cp_async16(uint32_t dst, const void* src) {
    asm volatile("cp.async.cg.shared.global [%0],[%1],16;" ::"r"(dst), "l"(src) : "memory");
}
DEVI uint4 ldg_nc128(const void* p) {
    uint4 v;
    asm volatile("ld.global.nc.L1::no_allocate.v4.u32 {%0,%1,%2,%3},[%4];" : "=r"(v.x), "=r"(v.y), "=r"(v.z), "=r"(v.w) : "l"(p));
    return v;
}
DEVI uint2 ldg_nc64(const void* p) {
    uint2 v;
    asm volatile("ld.global.nc.L1::no_allocate.v2.u32 {%0,%1},[%2];" : "=r"(v.x), "=r"(v.y) : "l"(p));
    return v;
}
template <int OFF>
DEVI void ldg128p(uint4& v, const void* p, bool pred) {
    asm volatile("{.reg .pred p; setp.ne.u32 p,%6,0; @p ld.global.L1::no_allocate.v4.u32 {%0,%1,%2,%3},[%4+%5];}"
                 : "=r"(v.x), "=r"(v.y), "=r"(v.z), "=r"(v.w) : "l"(p), "n"(OFF), "r"((uint32_t)pred) : "memory");
}
template <int OFF>
DEVI void ldg64p(uint2& v, const void* p, bool pred) {
    asm volatile("{.reg .pred p; setp.ne.u32 p,%4,0; @p ld.global.L1::no_allocate.v2.u32 {%0,%1},[%2+%3];}"
                 : "=r"(v.x), "=r"(v.y) : "l"(p), "n"(OFF), "r"((uint32_t)pred) : "memory");
}
template <int OFF>
DEVI void ldg128a(uint4& v, const void* p) {
    asm volatile("ld.global.v4.u32 {%0,%1,%2,%3},[%4+%5];" : "=r"(v.x), "=r"(v.y), "=r"(v.z), "=r"(v.w) : "l"(p), "n"(OFF) : "memory");
}
template <int OFF>
DEVI void load_pair(uint32_t& r0, uint32_t& r1, uint32_t& nd, uint32_t& msk, const uint8_t* base, uint32_t e, uint32_t idx) {
    const uint32_t np = e >> 12, pair = (e & 0xfffu) + min(idx, np);
    msk = idx < np ? 0u : 0x7f7fu;
    asm volatile("ld.relaxed.gpu.global.v2.u32 {%0,%1},[%3+%5];\n"
                 "ld.relaxed.gpu.global.u16 %2,[%4+%6];"
                 : "=r"(r0), "=r"(r1), "=r"(nd) : "l"(base + pair * 8), "l"(base + pair * 2), "n"(OFF), "n"(OFF + NODE_OFF) : "memory");
}
DEVI uint32_t rank_slot(uint32_t a, uint32_t tab) {
    uint32_t r;
    asm volatile("{.reg .pred p; setp.ne.u32 p,%1,0x7f; @p atom.shared.add.u32 %0,[%2],4;}" : "=r"(r) : "r"(a), "r"(tab + a * 4) : "memory");
    return r;
}
DEVI void place_slot(uint32_t a, uint32_t tab, uint32_t rk, uint32_t rec) {
    asm volatile("{.reg .pred p; .reg .b32 d; setp.ne.u32 p,%0,0x7f; @p ld.shared.u16 d,[%1]; @p add.u32 d,d,%2; @p st.shared.u32 [d],%3;}"
                 ::"r"(a), "r"(tab + a * 2), "r"(rk), "r"(rec) : "memory");
}
DEVI uint4 lds128(uint32_t a) {
    uint4 v;
    asm volatile("ld.shared.v4.u32 {%0,%1,%2,%3},[%4];" : "=r"(v.x), "=r"(v.y), "=r"(v.z), "=r"(v.w) : "r"(a) : "memory");
    return v;
}
DEVI void sts128(uint32_t a, uint4 v) {
    asm volatile("st.shared.v4.u32 [%0],{%1,%2,%3,%4};" ::"r"(a), "r"(v.x), "r"(v.y), "r"(v.z), "r"(v.w) : "memory");
}
DEVI uint4 ldg_row(uint32_t lo, uint32_t hi) {
    uint4 v;
    asm volatile("{.reg .b64 ad; mov.b64 ad,{%4,%5}; ld.global.v4.u32 {%0,%1,%2,%3},[ad];}"
                 : "=r"(v.x), "=r"(v.y), "=r"(v.z), "=r"(v.w) : "r"(lo), "r"(hi));
    return v;
}
DEVI void ldsm4(uint32_t& r0, uint32_t& r1, uint32_t& r2, uint32_t& r3, uint32_t a) {
    asm volatile("ldmatrix.sync.aligned.m8n8.x4.shared.b16 {%0,%1,%2,%3},[%4];"
                 : "=r"(r0), "=r"(r1), "=r"(r2), "=r"(r3) : "r"(a) : "memory");
}
DEVI void ldsm4t(uint32_t& r0, uint32_t& r1, uint32_t& r2, uint32_t& r3, uint32_t a) {
    asm volatile("ldmatrix.sync.aligned.m8n8.x4.trans.shared.b16 {%0,%1,%2,%3},[%4];"
                 : "=r"(r0), "=r"(r1), "=r"(r2), "=r"(r3) : "r"(a) : "memory");
}
DEVI void mma_bf16(float (&c)[4], uint32_t a0, uint32_t a1, uint32_t a2, uint32_t a3, uint32_t b0, uint32_t b1) {
    asm volatile("mma.sync.aligned.m16n8k16.row.col.f32.bf16.bf16.f32 {%0,%1,%2,%3},{%4,%5,%6,%7},{%8,%9},{%0,%1,%2,%3};"
                 : "+f"(c[0]), "+f"(c[1]), "+f"(c[2]), "+f"(c[3])
                 : "r"(a0), "r"(a1), "r"(a2), "r"(a3), "r"(b0), "r"(b1));
}
template <int ACC>
DEVI void wgmma_n96(float (&d)[48], uint32_t a, uint32_t bm) {
    asm volatile("{.reg .pred p; .reg .b64 da,db; setp.ne.b32 p,%50,0; mov.b64 da,{%48,0x40000040}; mov.b64 db,{%49,0x40000040};\n"
                 "wgmma.mma_async.sync.aligned.m64n96k16.f32.bf16.bf16 "
                 "{%0,%1,%2,%3,%4,%5,%6,%7,%8,%9,%10,%11,%12,%13,%14,%15,%16,%17,%18,%19,%20,%21,%22,%23,%24,%25,%26,%27,%28,%29,%30,%31,%32,%33,%34,%35,%36,%37,%38,%39,%40,%41,%42,%43,%44,%45,%46,%47},"
                 "da,db,p,1,1,1,0;}\n"
                 : "+f"(d[0]), "+f"(d[1]), "+f"(d[2]), "+f"(d[3]), "+f"(d[4]), "+f"(d[5]), "+f"(d[6]), "+f"(d[7]), "+f"(d[8]), "+f"(d[9]), "+f"(d[10]), "+f"(d[11]), "+f"(d[12]), "+f"(d[13]), "+f"(d[14]), "+f"(d[15]), "+f"(d[16]), "+f"(d[17]), "+f"(d[18]), "+f"(d[19]), "+f"(d[20]), "+f"(d[21]), "+f"(d[22]), "+f"(d[23]), "+f"(d[24]), "+f"(d[25]), "+f"(d[26]), "+f"(d[27]), "+f"(d[28]), "+f"(d[29]), "+f"(d[30]), "+f"(d[31]), "+f"(d[32]), "+f"(d[33]), "+f"(d[34]), "+f"(d[35]), "+f"(d[36]), "+f"(d[37]), "+f"(d[38]), "+f"(d[39]), "+f"(d[40]), "+f"(d[41]), "+f"(d[42]), "+f"(d[43]), "+f"(d[44]), "+f"(d[45]), "+f"(d[46]), "+f"(d[47])
                 : "r"(a), "r"(bm), "n"(ACC));
}
DEVI uint32_t pack_bf16(float lo, float hi) {
    uint32_t r;
    asm("cvt.rn.bf16x2.f32 %0,%1,%2;" : "=r"(r) : "f"(hi), "f"(lo));
    return r;
}
DEVI float bf_lo(uint32_t v) { return __uint_as_float(v << 16); }
DEVI float bf_hi(uint32_t v) { return __uint_as_float(v & 0xffff0000u); }
DEVI __nv_bfloat162 as_bf2(uint32_t v) { return *reinterpret_cast<__nv_bfloat162*>(&v); }
DEVI uint32_t as_u32(__nv_bfloat162 v) { return *reinterpret_cast<uint32_t*>(&v); }
DEVI uint32_t tanh_bf2(uint32_t a) {
    uint32_t d;
    asm("tanh.approx.bf16x2 %0,%1;" : "=r"(d) : "r"(a));
    return d;
}
DEVI uint32_t half_bf2(uint32_t v) { return as_u32(__hmul2(as_bf2(v), as_bf2(0x3f003f00u))); }

DEVI void edge_pre(uint32_t rec, const uint4& p, const uint32_t (&w)[4], const uint32_t (&q)[4], __nv_bfloat162 (&u)[4]) {
    const __nv_bfloat162 e2 = __high2bfloat162(as_bf2(rec));
    const uint32_t pw[4] = {p.x, p.y, p.z, p.w};
#pragma unroll
    for (int i = 0; i < 4; i++) u[i] = __hadd2(__hfma2(e2, as_bf2(w[i]), as_bf2(q[i])), as_bf2(pw[i]));
}
DEVI __nv_bfloat162 act(__nv_bfloat162 u) { return __hfma2(u, as_bf2(tanh_bf2(as_u32(u))), u); }

DEVI void wait_p(const uint8_t* smem, uint32_t v) {
    const uint32_t epoch = *reinterpret_cast<const volatile uint32_t*>(smem + SM_EP) + 1;
    int spins = 0;
    if (v != epoch * NB) {
        do {
            asm volatile("ld.acquire.gpu.global.u32 %0,[%1];" : "=r"(v) : "l"(&g_pcount) : "memory");
            if (++spins > (1 << 22)) __trap();
        } while ((int)(v - epoch * NB) < 0);
    }
    if (blockIdx.x == 0) g_epoch.x = epoch;
}
DEVI void store_partial(uint8_t* smem, int stream, int l16, const float (&acc)[8], uint32_t f) {
    float4* hp = reinterpret_cast<float4*>(smem + SM_H + stream * 512 + l16 * 16);
    hp[0] = make_float4(acc[0], acc[1], acc[2], acc[3]);
    hp[16] = make_float4(acc[4], acc[5], acc[6], acc[7]);
    asm volatile("fence.acq_rel.cta;" ::: "memory");
    __syncwarp(0xffffu << ((stream & 1) * 16));
    if (l16 == 0) *reinterpret_cast<volatile uint32_t*>(smem + SM_FLAG + stream * 4) = f;
}

template <bool SLOW>
DEVI bool sort_and_stream(uint8_t* smem, int& tid, const uint32_t (&rw)[9][2], const uint32_t (&nd)[9],
                          uint32_t plo, uint32_t phi, uint32_t dummy, int nn, bool first, bool tail, bool ovf,
                          float (&c)[2][4]) {
    const uint32_t sb = smem_u32(smem);
    int lane = tid & 31, warp = tid >> 5, l16 = lane & 15;
    uint32_t* hist2 = reinterpret_cast<uint32_t*>(smem + SM_HIST2);
    uint32_t* base2 = reinterpret_cast<uint32_t*>(smem + SM_BASE2);
    volatile uint32_t* flag = reinterpret_cast<volatile uint32_t*>(smem + SM_FLAG);
    uint32_t* sdeg = reinterpret_cast<uint32_t*>(smem + SM_DEG);
    constexpr int NMAIN = SLOW ? 4 : 6;
    uint32_t rk[9][2];
#pragma unroll
    for (int i = 0; i < NMAIN; i++) {
        rk[i][0] = rank_slot(nd[i] & 0x7fu, sb + SM_HIST2);
        rk[i][1] = rank_slot((nd[i] >> 8) & 0x7fu, sb + SM_HIST2);
    }
    if (!SLOW) {
#pragma unroll
        for (int i = 6; i < 9; i++) rk[i][0] = rk[i][1] = 0;
        if (tail) {
#pragma unroll
            for (int i = 6; i < 9; i++) {
                rk[i][0] = rank_slot(nd[i] & 0x7fu, sb + SM_HIST2);
                rk[i][1] = rank_slot((nd[i] >> 8) & 0x7fu, sb + SM_HIST2);
            }
        }
    }
    ovf = __syncthreads_or(ovf);
    stamp(6);
    const uint32_t lbeg = sb + SM_LIST, lend = lbeg + LIST_CAP * 4 - 64;
    if (warp == 0) {
        uint32_t cn[3], pg[3], sum = 0;
#pragma unroll
        for (int i = 0; i < 3; i++) {
            cn[i] = hist2[lane * 3 + i];
            pg[i] = (lane * 3 + i < nn) ? max((cn[i] + 12) & ~15u, 16u) : 0u;
            sum += pg[i];
        }
        uint32_t inc = sum;
#pragma unroll
        for (int o = 1; o < 32; o <<= 1) {
            const uint32_t v = __shfl_up_sync(0xffffffffu, inc, o);
            if (lane >= o) inc += v;
        }
        const uint32_t tot = lbeg + __shfl_sync(0xffffffffu, inc, 31);
        const bool fits = !ovf && tot <= lend;
        uint32_t run = lbeg + inc - sum;
        const uint4 d4 = make_uint4(dummy, dummy, dummy, dummy);
#pragma unroll
        for (int i = 0; i < 3; i++) {
            base2[lane * 3 + i] = run;
            reinterpret_cast<uint16_t*>(smem + SM_B16)[lane * 3 + i] = run - lbeg;
            run += pg[i];
            if (fits && pg[i]) sts128(run - 16, d4);
            sdeg[lane * 3 + i] = cn[i];
            if (SLOW && lane < 16) flag[lane * 3 + i] = 0;
            hist2[lane * 3 + i] = 0;
        }
        if (lane < 4) {
            base2[96 + lane] = tot;
            if (fits) sts128(tot + lane * 16, d4);
        }
        if (!SLOW) asm volatile("bar.arrive 2,64;" ::: "memory");
    }
    if (!SLOW && warp == 1) {
        asm volatile("bar.arrive 3,%0;" ::"n"(NT) : "memory");
        if (lane == 0) asm volatile("red.release.gpu.global.add.u32 [%0],1;" ::"l"(&g_pcount) : "memory");
        asm volatile("bar.sync 2,64;" ::: "memory");
    } else {
        asm volatile("bar.sync 3,%0;" ::"n"(NT) : "memory");
    }
    stamp(7);
    const uint32_t tot = base2[96];
    if (!SLOW && (ovf || tot > lend)) {
        if (tid == 0) wait_p(smem, 1u);
        __syncthreads();
        return false;
    }
#pragma unroll
    for (int i = 0; i < NMAIN; i++) {
        place_slot(nd[i] & 0x7fu, sb + SM_B16, rk[i][0] + lbeg, rw[i][0]);
        place_slot((nd[i] >> 8) & 0x7fu, sb + SM_B16, rk[i][1] + lbeg, rw[i][1]);
    }
    if (tail) {
#pragma unroll
        for (int i = 6; i < 9; i++) {
            place_slot(nd[i] & 0x7fu, sb + SM_B16, rk[i][0] + lbeg, rw[i][0]);
            place_slot((nd[i] >> 8) & 0x7fu, sb + SM_B16, rk[i][1] + lbeg, rw[i][1]);
        }
    }
    uint32_t pcnt = 1;
    __syncwarp();
    if (!SLOW && tid == NT - 32) asm volatile("ld.relaxed.gpu.global.u32 %0,[%1];" : "=r"(pcnt) : "l"(&g_pcount) : "memory");
    const uint32_t T2 = (tot - lbeg + 16) >> 5;
    const uint32_t per = T2 / NW, rem = T2 - per * NW;
    const int cnt = per + ((uint32_t)warp < rem);
    const uint32_t rs0 = lbeg + 32 * (warp * per + min((uint32_t)warp, rem)), rs1 = rs0 + 16 * cnt;
    int node;
    {
        int c0 = -1, c1 = -1;
#pragma unroll
        for (int i = 0; i < 3; i++) {
            const uint32_t gb = base2[lane + 32 * i];
            c0 += __popc(__ballot_sync(0xffffffffu, gb <= rs0));
            c1 += __popc(__ballot_sync(0xffffffffu, gb <= rs1));
        }
        node = lane < 16 ? c0 : c1;
    }
    uint32_t ri = lane < 16 ? rs0 : rs1;
    int dn = base2[node + 1] - ri;
    uint32_t qv[4], wv[4];
    {
        const uint4 w = lds128(sb + SM_WE + l16 * 16);
        wv[0] = half_bf2(w.x); wv[1] = half_bf2(w.y); wv[2] = half_bf2(w.z); wv[3] = half_bf2(w.w);
        const uint4 v = lds128(sb + SM_Q + node * 256 + ((l16 ^ (node & 7)) << 4));
        qv[0] = v.x; qv[1] = v.y; qv[2] = v.z; qv[3] = v.w;
    }
    asm volatile("cp.async.wait_group 0;" ::: "memory");
    if (!SLOW && tid == NT - 32) wait_p(smem, pcnt);
    __syncthreads();
    stamp(8);

    float acc[8];
    __nv_bfloat162 pend[4];
#pragma unroll
    for (int i = 0; i < 8; i++) acc[i] = 0.f;
    uint4 rA = lds128(ri), rB = lds128(ri + 16), A[4];
#define LOAD_GROUP(buf, r)                                         \
    {                                                              \
        buf[0] = ldg_row(__byte_perm(r.x, plo, 0x7104), phi);      \
        buf[1] = ldg_row(__byte_perm(r.y, plo, 0x7104), phi);      \
        buf[2] = ldg_row(__byte_perm(r.z, plo, 0x7104), phi);      \
        buf[3] = ldg_row(__byte_perm(r.w, plo, 0x7104), phi);      \
    }
#define COMPUTE_GROUP(buf, r, rn, off, MORE)                                                     \
    {                                                                                      \
        __nv_bfloat162 s0[4], s1[4], s2[4], s3[4];                                         \
        edge_pre(r.x, buf[0], wv, qv, s0);                                                 \
        edge_pre(r.y, buf[1], wv, qv, s1);                                                 \
        edge_pre(r.z, buf[2], wv, qv, s2);                                                 \
        edge_pre(r.w, buf[3], wv, qv, s3);                                                 \
        if (MORE) {                                                                        \
            LOAD_GROUP(buf, rn);                                                           \
            r = lds128(ri + off + 16);                                                     \
        }                                                                                  \
        {                                                                                  \
            _Pragma("unroll") for (int i = 0; i < 4; i++)                                  \
                s0[i] = __hadd2(__hadd2(act(s0[i]), act(s1[i])), __hadd2(act(s2[i]), act(s3[i]))); \
        }                                                                                  \
        const bool keep = MORE && off == 16;     \
        _Pragma("unroll") for (int i = 0; i < 4; i++) {                                    \
            if (off == 32) s0[i] = __hadd2(s0[i], pend[i]);                   \
            if (keep) {                                                                    \
                pend[i] = s0[i];                                                           \
            } else {                                                                       \
                acc[2 * i] += bf_lo(as_u32(s0[i]));                                        \
                acc[2 * i + 1] += bf_hi(as_u32(s0[i]));                                    \
            }                                                                              \
        }                                                                                  \
        if (dn == off) {     \
            if (keep) {                                                                    \
                _Pragma("unroll") for (int i = 0; i < 4; i++) {                            \
                    acc[2 * i] += bf_lo(as_u32(pend[i]));                                  \
                    acc[2 * i + 1] += bf_hi(as_u32(pend[i]));                              \
                    pend[i] = as_bf2(0u);                                                  \
                }                                                                          \
            }                                                                              \
            int tt;                                                                        \
            asm volatile("mov.u32 %0,%1;" : "=r"(tt) : "r"(tid));                          \
            if (node < 0) {                                                                \
                store_partial(smem, tt >> 4, tt & 15, acc, 1u);                            \
                node = ~node;                                                              \
            } else {                                                                       \
                sts128(sb + SM_S + node * S_STRIDE + (tt & 15) * 16,                       \
                       make_uint4(pack_bf16(acc[0], acc[1]), pack_bf16(acc[2], acc[3]),    \
                                  pack_bf16(acc[4], acc[5]), pack_bf16(acc[6], acc[7])));  \
            }                                                                              \
            node++;                                                                        \
            dn = base2[node + 1] - ri;                                                     \
            const uint4 v = lds128(sb + SM_Q + node * 256 + (((tt & 15) ^ (node & 7)) << 4)); \
            qv[0] = v.x; qv[1] = v.y; qv[2] = v.z; qv[3] = v.w;                            \
            _Pragma("unroll") for (int i = 0; i < 8; i++) acc[i] = 0.f;                    \
        }                                                                                  \
    }
    if (base2[node] != ri) node = ~node;
    LOAD_GROUP(A, rA);
    int left = cnt;
    if (SLOW) {
#pragma unroll 1
        for (; left > 0; left--) {
            COMPUTE_GROUP(A, rA, rA, 16, false);
            ri += 16;
            dn -= 16;
            rA = lds128(ri);
            LOAD_GROUP(A, rA);
        }
    } else {
#pragma unroll 1
        while (left >= 2) {
            COMPUTE_GROUP(A, rA, rB, 16, true);
            COMPUTE_GROUP(A, rB, rA, 32, true);
            ri += 32;
            dn -= 32;
            left -= 2;
        }
        if (left) {
            COMPUTE_GROUP(A, rA, rA, 16, false);
            ri += 16;
        }
    }
    stamp(9);
    asm volatile("" : "+r"(tid));
    lane = tid & 31; warp = tid >> 5; l16 = lane & 15;
    if (node < 0) store_partial(smem, tid >> 4, l16, acc, 2u);
    __syncwarp();
    if ((uint32_t)node < (uint32_t)min(NPC, N_NODES - (int)blockIdx.x * NPC) && base2[node] < ri) {
        uint32_t f;
        int st = tid >> 4;
        do {
            st++;
            int spins = 0;
            while ((f = flag[st]) == 0) {
                if (++spins > (1 << 24)) __trap();
            }
            asm volatile("fence.acq_rel.cta;" ::: "memory");
            const float4* hp = reinterpret_cast<const float4*>(smem + SM_H + st * 512 + l16 * 16);
            const float4 u0 = hp[0], u1 = hp[16];
            acc[0] += u0.x; acc[1] += u0.y; acc[2] += u0.z; acc[3] += u0.w;
            acc[4] += u1.x; acc[5] += u1.y; acc[6] += u1.z; acc[7] += u1.w;
        } while (f == 2u);
        sts128(sb + SM_S + node * S_STRIDE + l16 * 16,
               make_uint4(pack_bf16(acc[0], acc[1]), pack_bf16(acc[2], acc[3]), pack_bf16(acc[4], acc[5]), pack_bf16(acc[6], acc[7])));
    }
    __syncwarp();
    const int mt = warp >> 2, nq = warp & 3;
    uint32_t wf[8][4];
    const uint32_t wa = sb + SM_W2 + l16 * 128 + (((nq * 2 + (lane >> 4)) ^ (lane & 7)) << 4);
#pragma unroll
    for (int s = 0; s < 8; s++) ldsm4t(wf[s][0], wf[s][1], wf[s][2], wf[s][3], wa + s * 2048);
    {
        const float d0 = 0.25f * (float)sdeg[mt * 16 + (lane >> 2)], d1 = 0.25f * (float)sdeg[mt * 16 + 8 + (lane >> 2)];
#pragma unroll
        for (int j = 0; j < 2; j++) {
            const uint32_t bb = reinterpret_cast<const uint32_t*>(smem + SM_B2)[nq * 8 + j * 4 + (lane & 3)];
            if (first) c[j][0] = c[j][1] = c[j][2] = c[j][3] = 0.f;
            c[j][0] += d0 * bf_lo(bb); c[j][1] += d0 * bf_hi(bb);
            c[j][2] += d1 * bf_lo(bb); c[j][3] += d1 * bf_hi(bb);
        }
    }
    const uint32_t sa = sb + SM_S + (mt * 16 + l16) * S_STRIDE + (lane >> 4) * 16;
    __syncthreads();
    stamp(10);
#pragma unroll
    for (int s = 0; s < 8; s++) {
        uint32_t a0, a1, a2, a3;
        ldsm4(a0, a1, a2, a3, sa + s * 32);
        mma_bf16(c[0], a0, a1, a2, a3, wf[s][0], wf[s][1]);
        mma_bf16(c[1], a0, a1, a2, a3, wf[s][2], wf[s][3]);
    }
    return true;
}

DEVI void store_out(__nv_bfloat16* out, const float (&c)[2][4], int tid) {
    const int n0 = blockIdx.x * NPC, nn = min(NPC, N_NODES - n0);
    const int row0 = (tid >> 7) * 16 + ((tid & 31) >> 2);
    uint32_t* o = reinterpret_cast<uint32_t*>(out) + (n0 + row0) * 32 + ((tid >> 5) & 3) * 8 + (tid & 3);
#pragma unroll
    for (int j = 0; j < 2; j++) {
        if (row0 < nn) o[j * 4] = pack_bf16(c[j][0], c[j][1]);
        if (row0 + 8 < nn) o[j * 4 + 8 * 32] = pack_bf16(c[j][2], c[j][3]);
    }
}

__device__ __noinline__ void slow_path(uint8_t* smem, const __nv_bfloat16* ea, const int* src, const int* dst,
                                       __nv_bfloat16* out, uint64_t pbase) {
    int tid = threadIdx.x;
    const int l16 = tid & 15, n0 = blockIdx.x * NPC, nn = min(NPC, N_NODES - n0);
    const uint32_t rowc = ((uint32_t)pbase >> 8) & 0xc000u;
    const uint32_t plo = ((uint32_t)pbase & 0xff000000u) | (l16 * 16), phi = (uint32_t)(pbase >> 32);
    uint32_t rw[9][2], nd[9];
    float c[2][4];
#pragma unroll 1
    for (int round = 0; round < SLOW_ROUNDS; round++) {
#pragma unroll
        for (int h = 0; h < 2; h++) {
            const int q = (round * 2 + h) * NT + tid;
            const int qq = min(q, QUADS - 1);
            const uint4 d4 = ldg_nc128(reinterpret_cast<const uint4*>(dst) + qq);
            const uint4 s4 = ldg_nc128(reinterpret_cast<const uint4*>(src) + qq);
            const uint2 e4 = ldg_nc64(reinterpret_cast<const uint2*>(ea) + qq);
            rw[2 * h][0] = __byte_perm(s4.x | rowc, e4.x, 0x5410);
            rw[2 * h][1] = __byte_perm(s4.y | rowc, e4.x, 0x7610);
            rw[2 * h + 1][0] = __byte_perm(s4.z | rowc, e4.y, 0x5410);
            rw[2 * h + 1][1] = __byte_perm(s4.w | rowc, e4.y, 0x7610);
            const uint32_t lim = q < QUADS ? NPC : 0;
            const uint32_t a0 = d4.x - n0, a1 = d4.y - n0, a2 = d4.z - n0, a3 = d4.w - n0;
            nd[2 * h] = (a0 < lim ? a0 : 0x7fu) | ((a1 < lim ? a1 : 0x7fu) << 8);
            nd[2 * h + 1] = (a2 < lim ? a2 : 0x7fu) | ((a3 < lim ? a3 : 0x7fu) << 8);
        }
        sort_and_stream<true>(smem, tid, rw, nd, plo, phi, rowc | N_NODES, nn, round == 0, false, false, c);
    }
    store_out(out, c, tid);
}

__global__ void __launch_bounds__(NT, 1)
mpnn_kernel(const __nv_bfloat16* __restrict__ x, const __nv_bfloat16* __restrict__ ea,
            const int* __restrict__ src, const int* __restrict__ dst,
            const __nv_bfloat16* __restrict__ w1, const __nv_bfloat16* __restrict__ b1,
            const __nv_bfloat16* __restrict__ w2, const __nv_bfloat16* __restrict__ b2,
            __nv_bfloat16* __restrict__ out) {
    extern __shared__ __align__(1024) uint8_t smem[];
    const uint32_t sb = smem_u32(smem);
    int tid;
    asm volatile("shfl.sync.bfly.b32 %0,%1,0,31,0xffffffff;" : "=r"(tid) : "r"(threadIdx.x));
    const int lane = tid & 31, warp = tid >> 5;
    const int b = blockIdx.x;
    const int g = lane >> 2;
    const int n0 = b * NPC;
    const int nn = min(NPC, N_NODES - n0);
    uint32_t* hist = reinterpret_cast<uint32_t*>(smem + SM_HIST);
    stamp(0);

    const int q0 = b * 1515 + min(b, 20) + tid;
    const bool has2 = tid < 1515 - NT + (b < 20);
    uint4 vd[2], vs[2];
    uint2 ve[2];
    ldg128p<0>(vd[0], reinterpret_cast<const uint4*>(dst) + q0, true);
    ldg128p<NT * 16>(vd[1], reinterpret_cast<const uint4*>(dst) + q0, has2);
    if (tid >= NT - 64) {
        const int i = tid - (NT - 64);
        const uint8_t* p = i < 16 ? reinterpret_cast<const uint8_t*>(b1) + i * 16
                         : i < 32 ? reinterpret_cast<const uint8_t*>(w1) + 32768 - 256 + i * 16
                         : i < 40 ? reinterpret_cast<const uint8_t*>(b2) - 512 + i * 16
                                  : reinterpret_cast<const uint8_t*>(&g_epoch);
        if (i <= 40) cp_async16(sb + SM_B1 + i * 16, p);
    }
    asm volatile("cp.async.commit_group;" ::: "memory");
    if (tid < (SM_TOTAL - SM_HIST) / 4) hist[tid] = 0;
    __syncthreads();
    ldg128p<0>(vs[0], reinterpret_cast<const uint4*>(src) + q0, true);
    ldg64p<0>(ve[0], reinterpret_cast<const uint2*>(ea) + q0, true);
    ldg128p<NT * 16>(vs[1], reinterpret_cast<const uint4*>(src) + q0, has2);
    ldg64p<NT * 8>(ve[1], reinterpret_cast<const uint2*>(ea) + q0, has2);
    asm volatile("bar.sync 1,%0;" ::"n"(NT) : "memory");

    const uint32_t* dd = reinterpret_cast<const uint32_t*>(vd);
    uint32_t rk0[8];
#pragma unroll
    for (int i = 0; i < 8; i++) {
        asm volatile("{.reg .pred p; setp.ne.u32 p,%2,0; @p atom.shared.add.u32 %0,[%1],1;}"
                     : "=r"(rk0[i]) : "r"(sb + SM_HIST + __umulhi(dd[i], OWN_M) * 4), "r"((uint32_t)(i < 4 || has2)) : "memory");
    }
    cp_async16(sb + SM_X + (tid >> 3) * 128 + (((tid ^ (tid >> 3)) & 7) << 4),
               reinterpret_cast<const uint8_t*>(x) + min(n0 * 8 + tid, N_NODES * 8 - 1) * 16);
#pragma unroll
    for (int k = 0; k < 3; k++) {
        if (k < 2 || tid < 2048 - 2 * NT)
            cp_async16(sb + SM_W1 + k * 6144 + (tid & 8) * 2048 + (tid >> 4) * 128 + (((tid ^ (tid >> 4)) & 7) << 4),
                       reinterpret_cast<const uint8_t*>(w1) + (tid + k * NT) * 16);
    }
    asm volatile("cp.async.commit_group;" ::: "memory");
    asm volatile("cp.async.wait_group 1;" ::: "memory");
    __syncthreads();
    stamp(1);
    const uint32_t epoch = *reinterpret_cast<const uint32_t*>(smem + SM_EP) + 1;
    const uint32_t par = epoch & 1;
    uint32_t fill = 0x7f7f7f7fu | (par * 0x80808080u);
    asm volatile("" : "+r"(fill));
    uint16_t* base = reinterpret_cast<uint16_t*>(smem + SM_BASE);
    uint64_t pbase = (reinterpret_cast<uint64_t>(g_Pbuf) + 0x3fffffu) & ~(uint64_t)0x3fffffu;
    if ((((uint32_t)pbase >> 23) & 1) != par) pbase += 0x800000u;
    const uint32_t rowc = ((uint32_t)pbase >> 8) & 0xc000u;
    if (warp == 16) {
        uint32_t cn[5], sum = 0;
#pragma unroll
        for (int i = 0; i < 5; i++) { cn[i] = (hist[lane * 5 + i] + 1) & ~1u; sum += cn[i]; }
        uint32_t inc = sum;
#pragma unroll
        for (int o = 1; o < 32; o <<= 1) {
            const uint32_t v = __shfl_up_sync(0xffffffffu, inc, o);
            if (lane >= o) inc += v;
        }
        uint32_t run = inc - sum;
#pragma unroll
        for (int i = 0; i < 5; i++) {
            base[lane * 5 + i] = run;
            run += cn[i];
            if (cn[i]) smem[SM_STAGE + NODE_OFF + run - 1] = (uint8_t)fill;
        }
    } else if (warp == 17 || warp == 18) {
        const int i = tid - 17 * 32;
        if (i < 50) sts128(sb + SM_STAGE + (i < 40 ? 6048 * 4 + i * 16 : NODE_OFF + 6048 - 640 + i * 16), make_uint4(fill, fill, fill, fill));
    } else if (warp == 19 && b == 0 && lane < 16) {
        asm volatile("st.global.v4.u32 [%0],{%1,%1,%1,%1};" ::"l"(pbase + N_NODES * 256 + lane * 16), "r"(0xff00ff00u) : "memory");
    }
    __syncthreads();
    stamp(2);
    if (warp == 18) {
        uint32_t en[5];
#pragma unroll
        for (int i = 0; i < 5; i++) {
            const uint32_t o = base[lane + 32 * i], e = base[lane + 32 * i + 1];
            en[i] = (o >> 1) | ((e - o) << 11) | (epoch << 24);
        }
        uint32_t* tp = &g_tab[lane * TAB_STRIDE + (b % NW) * 8 + b / NW];
#pragma unroll
        for (int i = 0; i < 5; i++) {
            if (lane + 32 * i < NB)
                asm volatile("st.relaxed.gpu.global.u32 [%0],%1;" ::"l"(tp + 32 * i * TAB_STRIDE), "r"(en[i]) : "memory");
        }
    }
    {
        const uint32_t* ss = reinterpret_cast<const uint32_t*>(vs);
        const uint32_t* ee = reinterpret_cast<const uint32_t*>(ve);
#pragma unroll
        for (int h = 0; h < 2; h++) {
            if (h == 0 || has2) {
#pragma unroll
                for (int i = h * 4; i < h * 4 + 4; i++) {
                    const uint32_t own = __umulhi(dd[i], OWN_M);
                    const uint32_t pos = base[own] + rk0[i];
                    smem[SM_STAGE + NODE_OFF + pos] = (uint8_t)(dd[i] + (par << 7) - own * NPC);
                    reinterpret_cast<uint32_t*>(smem + SM_STAGE)[pos] = __byte_perm(ss[i] | rowc, ee[i >> 1], (i & 1) ? 0x7610 : 0x5410);
                }
            }
        }
        asm volatile("cp.async.wait_group 0;" ::: "memory");
        __syncthreads();
        stamp(3);
        if (warp < 16) asm volatile("fence.proxy.async.shared::cta;" ::: "memory");

    }
    uint32_t ent = epoch << 24;
    const uint32_t* tabp = &g_tab[b * TAB_STRIDE + warp * 8 + lane];
    if (warp >= 16) {
        uint4 v[8];
#pragma unroll
        for (int k = 0; k < 8; k++) v[k] = lds128(sb + SM_STAGE + (tid - 512) * 16 + k * 4096);
#pragma unroll
        for (int k = 0; k < 8; k++) if (k < 7 || tid - 512 < STAGEB / 16 - 7 * 256) g_rec[b * (STAGEB / 16) + tid - 512 + k * 256] = v[k];
    }
    if (warp + NW * lane < NB) asm volatile("ld.relaxed.gpu.global.u32 %0,[%1];" : "=r"(ent) : "l"(tabp) : "memory");
    if (warp < 16) {
        const int wg = __shfl_sync(0xffffffffu, warp >> 2, 0);
        const uint32_t xa = ((sb + SM_X) >> 4) | 0x10000u, wa = ((sb + SM_W1 + (wg >> 1) * 8192 + (wg & 1) * 16384) >> 4) | 0x10000u;
        float d[48];
        asm volatile("wgmma.fence.sync.aligned;" ::: "memory");
        wgmma_n96<0>(d, wa, xa);
        wgmma_n96<1>(d, wa + 128, xa + 2);
        wgmma_n96<1>(d, wa + 256, xa + 4);
        wgmma_n96<1>(d, wa + 384, xa + 6);
        asm volatile("wgmma.commit_group.sync.aligned;" ::: "memory");
        const __nv_bfloat16* bp = reinterpret_cast<const __nv_bfloat16*>(smem + SM_B1) + (warp & 7) * 16 + g;
        const float hb = warp < 8 ? 0.f : 0.5f, bb0 = hb * __bfloat162float(bp[0]), bb1 = hb * __bfloat162float(bp[8]);
        const uint32_t qa = sb + (warp < 8 ? SM_P : SM_Q) + ((lane >> 4) * 8 + (lane & 7)) * 256 +
                            ((((warp & 7) * 2 + ((lane >> 3) & 1)) ^ (lane & 7)) << 4);
        asm volatile("wgmma.wait_group.sync.aligned 0;" ::: "memory");
#pragma unroll
        for (int j = 0; j < 6; j++) {
            const float* dj = d + j * 8;
            asm volatile("stmatrix.sync.aligned.m8n8.x4.trans.shared.b16 [%0],{%1,%2,%3,%4};" ::"r"(qa + j * 4096),
                         "r"(pack_bf16(fmaf(dj[0], 0.5f, bb0), fmaf(dj[1], 0.5f, bb0))), "r"(pack_bf16(fmaf(dj[2], 0.5f, bb1), fmaf(dj[3], 0.5f, bb1))),
                         "r"(pack_bf16(fmaf(dj[4], 0.5f, bb0), fmaf(dj[5], 0.5f, bb0))), "r"(pack_bf16(fmaf(dj[6], 0.5f, bb1), fmaf(dj[7], 0.5f, bb1))) : "memory");
        }
    }
    __syncthreads();
    if (warp < 16) {
#pragma unroll
        for (int k = 0; k < 2; k++) {
            const int pos = (tid >> 3) + 64 * k, ck = tid & 7;
            cp_async16(sb + SM_W2 + pos * 128 + ((ck ^ (pos & 7)) << 4), reinterpret_cast<const uint8_t*>(w2) + pos * 128 + ck * 16);
        }
        asm volatile("cp.async.commit_group;" ::: "memory");
    }
    __syncwarp();
    const int l16 = lane & 15;
    const uint32_t plo = ((uint32_t)pbase & 0xff000000u) | (l16 * 16), phi = (uint32_t)(pbase >> 32);
    const uint32_t dummy = rowc | N_NODES;
    stamp(4);

    uint32_t rw[9][2], nd[9];
    bool tail, ovf;
    {
        {
            int spins = 0;
            while ((ent >> 24) != (epoch & 0xffu)) {
                asm volatile("ld.relaxed.gpu.global.u32 %0,[%1];" : "=r"(ent) : "l"(tabp) : "memory");
                if (++spins > (1 << 22)) __trap();
            }
            ent &= 0xffffffu;
        }
        __syncwarp();
        stamp(13);
        tail = __any_sync(0xffffffffu, ent >= (33u << 12));
        ovf = ent >= (49u << 12);
        const uint8_t* ra = reinterpret_cast<const uint8_t*>(g_rec) + warp * STAGEB;
        asm volatile("" : "+l"(ra));
        int spins = 0;
        bool bad;
        do {
            constexpr int W = NW * STAGEB;
            uint32_t mk[9];
            load_pair<0 * W>(rw[0][0], rw[0][1], nd[0], mk[0], ra, __shfl_sync(0xffffffffu, ent, 0), lane);
            load_pair<1 * W>(rw[1][0], rw[1][1], nd[1], mk[1], ra, __shfl_sync(0xffffffffu, ent, 1), lane);
            load_pair<2 * W>(rw[2][0], rw[2][1], nd[2], mk[2], ra, __shfl_sync(0xffffffffu, ent, 2), lane);
            load_pair<3 * W>(rw[3][0], rw[3][1], nd[3], mk[3], ra, __shfl_sync(0xffffffffu, ent, 3), lane);
            load_pair<4 * W>(rw[4][0], rw[4][1], nd[4], mk[4], ra, __shfl_sync(0xffffffffu, ent, 4), lane);
            load_pair<0>(rw[5][0], rw[5][1], nd[5], mk[5], ra + (warp < NB - 5 * NW ? 5 * W : 0), __shfl_sync(0xffffffffu, ent, 5), lane);
            uint32_t m = 0;
            if (tail) {
                const uint8_t* rb = ra + (lane >> 4) * W;
                load_pair<0 * W>(rw[6][0], rw[6][1], nd[6], mk[6], rb, __shfl_sync(0xffffffffu, ent, 0 + (lane >> 4)), l16 + 32);
                load_pair<2 * W>(rw[7][0], rw[7][1], nd[7], mk[7], rb, __shfl_sync(0xffffffffu, ent, 2 + (lane >> 4)), l16 + 32);
                load_pair<4 * W>(rw[8][0], rw[8][1], nd[8], mk[8], warp < NB - 5 * NW ? rb : ra, __shfl_sync(0xffffffffu, ent, 4 + (lane >> 4)), l16 + 32);
#pragma unroll
                for (int i = 6; i < 9; i++) { m |= (rw[i][0] ^ fill) | (nd[i] ^ fill); nd[i] |= mk[i]; }
            } else {
#pragma unroll
                for (int i = 6; i < 9; i++) rw[i][0] = rw[i][1] = nd[i] = 0;
            }
            if (spins == 0) {
                __syncthreads();
#pragma unroll
                for (int k = 0; k < 2; k++) {
                    const int row = (tid >> 4) + 48 * k;
                    const uint4 v = lds128(sb + SM_P + row * 256 + ((l16 ^ (row & 7)) << 4));
                    if (row < nn) asm volatile("st.global.v4.u32 [%0],{%1,%2,%3,%4};" ::"l"(pbase + (n0 * 16 + tid + k * NT) * 16), "r"(v.x), "r"(v.y), "r"(v.z), "r"(v.w) : "memory");
                }
            }
#pragma unroll
            for (int i = 0; i < 6; i++) { m |= (rw[i][0] ^ fill) | (nd[i] ^ fill); nd[i] |= mk[i]; }
            bad = __any_sync(0xffffffffu, m & 0x8000u);
            if (spins == 0) stamp(11);
            if (++spins > (1 << 20)) __trap();
        } while (bad);
    }
    stamp(5);
    float c[2][4];
    if (!sort_and_stream<false>(smem, tid, rw, nd, plo, phi, dummy, nn, true, tail, ovf, c)) {
        slow_path(smem, ea, src, dst, out, pbase);
        return;
    }
    store_out(out, c, tid);
    stamp(12);
}

}

extern "C" void kernel_launch(void* const* d_in, const int* in_sizes, int n_in, void* d_out, int out_size) {
    (void)in_sizes; (void)n_in; (void)out_size;
    static bool configured = false;
    if (!configured) {
        cudaFuncSetAttribute(mpnn_kernel, cudaFuncAttributeMaxDynamicSharedMemorySize, SM_TOTAL);
        configured = true;
    }
    mpnn_kernel<<<NB, NT, SM_TOTAL>>>(
        (const __nv_bfloat16*)d_in[0], (const __nv_bfloat16*)d_in[1], (const int*)d_in[2], (const int*)d_in[3],
        (const __nv_bfloat16*)d_in[4], (const __nv_bfloat16*)d_in[5], (const __nv_bfloat16*)d_in[6],
        (const __nv_bfloat16*)d_in[7], (__nv_bfloat16*)d_out);
}
```
